```python
import torch

def _softmax(x, axis=-1):
    return torch.softmax(x, dim=axis)

def _gelu(x):
    return torch.nn.functional.gelu(x, approximate='tanh')

def _silu(x):
    return torch.nn.functional.silu(x)

def _sigmoid(x):
    return torch.sigmoid(x)

def _layernorm(x, axis=-1, eps=1e-05):
    m = x.mean(dim=axis, keepdim=True)
    v = x.var(dim=axis, keepdim=True, unbiased=False)
    return (x - m) / torch.sqrt(v + eps)

def _scatter_add(tgt, idx, src, axis=0):
    return tgt.clone().index_add_(axis, idx, src)

def _segment_sum(src, seg, n):
    out = torch.zeros((n,) + src.shape[1:], dtype=src.dtype)
    return out.index_add_(0, seg, src)

def _pad(x, pw):
    flat = tuple((v for pair in reversed(pw) for v in pair))
    return torch.nn.functional.pad(x, flat)
kernel_name = 'recurrent_scan__memory_aug_recurrent_mem_tr__swiglu_ffn__prompt'

def setup_inputs():

    _w = lambda a: (lambda t: t.to(torch.bfloat16) if t.is_floating_point() else t)(torch.as_tensor(a))

    def _A_setup():
        B, S, Dm = (1, 2048, 448)
        H, Dh = (16, 256)
        M, seg = (8, 32)
        seg = min(seg, S)
        S = S // seg * seg
        return {'x': _w((lambda *s: torch.randn(*s, dtype=torch.bfloat16) * 0.05)(B, S, Dm)), 'mem0': _w((lambda *s: torch.randn(*s, dtype=torch.bfloat16) * 0.2)(B, M, Dm)), 'Wq': _w((lambda *s: torch.randn(*s, dtype=torch.bfloat16) * 1.6)(Dm, H, Dh) * Dm ** (-0.5)), 'Wk': _w((lambda *s: torch.randn(*s, dtype=torch.bfloat16) * 1.6)(Dm, H, Dh) * Dm ** (-0.5)), 'Wv': _w((lambda *s: torch.randn(*s, dtype=torch.bfloat16) * 0.2)(Dm, H, Dh) * Dm ** (-0.5)), 'Wo': _w((lambda *s: torch.randn(*s, dtype=torch.bfloat16) * 0.2)(H, Dh, Dm) * (H * Dh) ** (-0.5)), 'seg_len': seg}
    _A_in = _A_setup()

    def _B_setup():
        B, S, D, F = (1, 2048, 448, 1792)
        return {'x': _w((lambda *s: torch.randn(*s, dtype=torch.bfloat16) * 0.05)(B, S, D)), 'w_gate': _w((lambda *s: torch.randn(*s, dtype=torch.bfloat16) * 0.1)(D, F)), 'w_up': _w((lambda *s: torch.randn(*s, dtype=torch.bfloat16) * 0.1)(D, F)), 'w_down': _w((lambda *s: torch.randn(*s, dtype=torch.bfloat16) * 0.1)(F, D))}
    _B_in = _B_setup()
    return {'A_x': _A_in['x'], 'A_mem0': _A_in['mem0'], 'A_Wq': _A_in['Wq'], 'A_Wk': _A_in['Wk'], 'A_Wv': _A_in['Wv'], 'A_Wo': _A_in['Wo'], 'A_seg_len': _A_in['seg_len'], 'B_x': _B_in['x'], 'B_w_gate': _B_in['w_gate'], 'B_w_up': _B_in['w_up'], 'B_w_down': _B_in['w_down']}

def reference(A_x, A_mem0, A_Wq, A_Wk, A_Wv, A_Wo, A_seg_len, B_x, B_w_gate, B_w_up, B_w_down):

    def _A_ref(x, mem0, Wq, Wk, Wv, Wo, seg_len):
        B, S, Dm = x.shape
        H, Dh = (Wq.shape[1], Wq.shape[2])
        M = mem0.shape[1]
        scale = Dh ** (-0.5)
        n_seg = S // seg_len
        L = M + seg_len
        idx = torch.arange(L)
        mask = (idx[:, None] < M) | (idx[:, None] >= idx[None, :])
        mem = mem0
        outs = []
        for s in range(n_seg):
            xs = x[:, s * seg_len:(s + 1) * seg_len, :].clone()
            h = torch.concatenate([mem, xs], axis=1)
            q = torch.einsum('btd,dhe->bhte', h, Wq)
            k = torch.einsum('btd,dhe->bhte', h, Wk)
            v = torch.einsum('btd,dhe->bhte', h, Wv)
            scores = torch.einsum('bhqe,bhke->bhqk', q, k) * scale
            scores = torch.where(mask[None, None], scores, -1000000000.0)
            p = _softmax(scores, axis=-1)
            o = torch.einsum('bhqk,bhke->bhqe', p, v)
            o = torch.einsum('bhte,hed->btd', o, Wo)
            mem = o[:, :M, :].clone()
            outs.append(o[:, M:, :])
        return torch.concatenate(outs, axis=1)

    def _B_ref(x, w_gate, w_up, w_down):
        g = _silu(x @ w_gate)
        u = x @ w_up
        return g * u @ w_down
    x = A_x
    xn = _layernorm(x, axis=-1)
    s = _A_ref(xn, A_mem0, A_Wq, A_Wk, A_Wv, A_Wo, A_seg_len)
    g = _silu(_B_ref(xn, B_w_gate, B_w_up, B_w_down))
    return x + s * g
```

```cpp
#include <cuda_runtime.h>
#include <cuda_bf16.h>
#include <cuda.h>
#include <stdint.h>
#include <type_traits>

constexpr int SEQ = 2048, DM = 448, NH = 16, DH = 256, SEG = 32, NSEG = 64, FF = 1792;

__device__ __forceinline__ uint32_t smem_u32(const void* p) { return (uint32_t)__cvta_generic_to_shared(p); }
__device__ __forceinline__ uint32_t mapa(uint32_t a, uint32_t r) {
  uint32_t o; asm("mapa.shared::cluster.u32 %0, %1, %2;" : "=r"(o) : "r"(a), "r"(r)); return o;
}
__device__ __forceinline__ void cluster_sync_all() {
  asm volatile("barrier.cluster.arrive.release.aligned;\n barrier.cluster.wait.acquire.aligned;" ::: "memory");
}
__device__ __forceinline__ void mbar_init(uint32_t b, uint32_t cnt) {
  asm volatile("mbarrier.init.shared::cta.b64 [%0], %1;" ::"r"(b), "r"(cnt) : "memory");
}
__device__ __forceinline__ void mbar_expect(uint32_t b, uint32_t bytes) {
  asm volatile("mbarrier.arrive.expect_tx.shared::cta.b64 _, [%0], %1;" ::"r"(b), "r"(bytes) : "memory");
}
__device__ __forceinline__ void mbar_arrive(uint32_t b) {
  asm volatile("mbarrier.arrive.shared::cta.b64 _, [%0];" ::"r"(b) : "memory");
}
constexpr uint32_t SPIN_LIMIT = 1u << 15, POLL_LIMIT = 1u << 16, DEP_LIMIT = 1u << 19, GATE_LIMIT = 1u << 21;
__device__ __forceinline__ void mbar_wait(uint32_t b, uint32_t par) {
  asm volatile(
      "{\n .reg .pred p, q;\n .reg .u32 n;\n mov.u32 n, 0;\n"
      "W:\n mbarrier.try_wait.parity.shared::cta.b64 p, [%0], %1;\n"
      " @p bra D;\n add.u32 n, n, 1;\n setp.lt.u32 q, n, %2;\n @q bra W;\n"
      "D:\n}" ::"r"(b), "r"(par), "n"(SPIN_LIMIT) : "memory");
}
__device__ __forceinline__ bool elect_one() {
  uint32_t p;
  asm volatile("{\n .reg .pred q;\n elect.sync _|q, 0xffffffff;\n selp.u32 %0, 1, 0, q;\n}" : "=r"(p));
  return p != 0;
}
__device__ __forceinline__ void bar_sync(int id, int n) { asm volatile("bar.sync %0, %1;" ::"r"(id), "r"(n) : "memory"); }
__device__ __forceinline__ void bar_arrive(int id, int n) { asm volatile("bar.arrive %0, %1;" ::"r"(id), "r"(n) : "memory"); }

__device__ __forceinline__ void ldsm4(uint32_t& a, uint32_t& b, uint32_t& c, uint32_t& d, uint32_t addr) {
  asm volatile("ldmatrix.sync.aligned.m8n8.x4.shared.b16 {%0,%1,%2,%3}, [%4];" : "=r"(a), "=r"(b), "=r"(c), "=r"(d) : "r"(addr) : "memory");
}
__device__ __forceinline__ void ldsm2(uint32_t& a, uint32_t& b, uint32_t addr) {
  asm volatile("ldmatrix.sync.aligned.m8n8.x2.shared.b16 {%0,%1}, [%2];" : "=r"(a), "=r"(b) : "r"(addr) : "memory");
}
__device__ __forceinline__ void ldsm4t(uint32_t& a, uint32_t& b, uint32_t& c, uint32_t& d, uint32_t addr) {
  asm volatile("ldmatrix.sync.aligned.m8n8.x4.trans.shared.b16 {%0,%1,%2,%3}, [%4];" : "=r"(a), "=r"(b), "=r"(c), "=r"(d) : "r"(addr) : "memory");
}
__device__ __forceinline__ void ldsm2t(uint32_t& a, uint32_t& b, uint32_t addr) {
  asm volatile("ldmatrix.sync.aligned.m8n8.x2.trans.shared.b16 {%0,%1}, [%2];" : "=r"(a), "=r"(b) : "r"(addr) : "memory");
}
__device__ __forceinline__ void stsm2t(uint32_t addr, uint32_t a, uint32_t b) {
  asm volatile("stmatrix.sync.aligned.m8n8.x2.trans.shared.b16 [%0], {%1,%2};" ::"r"(addr), "r"(a), "r"(b) : "memory");
}
__device__ __forceinline__ void stsm4(uint32_t addr, uint32_t a, uint32_t b, uint32_t c, uint32_t d) {
  asm volatile("stmatrix.sync.aligned.m8n8.x4.shared.b16 [%0], {%1,%2,%3,%4};" ::"r"(addr), "r"(a), "r"(b), "r"(c), "r"(d) : "memory");
}
__device__ __forceinline__ void stsm4t(uint32_t addr, uint32_t a, uint32_t b, uint32_t c, uint32_t d) {
  asm volatile("stmatrix.sync.aligned.m8n8.x4.trans.shared.b16 [%0], {%1,%2,%3,%4};" ::"r"(addr), "r"(a), "r"(b), "r"(c), "r"(d) : "memory");
}
__device__ __forceinline__ void sts32(uint32_t addr, uint32_t v) { asm volatile("st.shared.u32 [%0], %1;" ::"r"(addr), "r"(v) : "memory"); }
__device__ __forceinline__ uint32_t lds32(uint32_t addr) { uint32_t v; asm volatile("ld.shared.u32 %0, [%1];" : "=r"(v) : "r"(addr) : "memory"); return v; }

__device__ __forceinline__ void mma16(float (&c)[4], uint32_t a0, uint32_t a1, uint32_t a2, uint32_t a3, uint32_t b0, uint32_t b1) {
  asm("mma.sync.aligned.m16n8k16.row.col.f32.bf16.bf16.f32 {%0,%1,%2,%3},{%4,%5,%6,%7},{%8,%9},{%0,%1,%2,%3};"
      : "+f"(c[0]), "+f"(c[1]), "+f"(c[2]), "+f"(c[3]) : "r"(a0), "r"(a1), "r"(a2), "r"(a3), "r"(b0), "r"(b1));
}
__device__ __forceinline__ void mma16v(float (&c)[4], const uint32_t (&a)[4], uint32_t b0, uint32_t b1) {
  asm volatile("mma.sync.aligned.m16n8k16.row.col.f32.bf16.bf16.f32 {%0,%1,%2,%3},{%4,%5,%6,%7},{%8,%9},{%0,%1,%2,%3};"
      : "+f"(c[0]), "+f"(c[1]), "+f"(c[2]), "+f"(c[3]) : "r"(a[0]), "r"(a[1]), "r"(a[2]), "r"(a[3]), "r"(b0), "r"(b1));
}
__device__ __forceinline__ void sts128(uint32_t addr, float a, float b, float c, float d) {
  asm volatile("st.shared.v4.f32 [%0], {%1,%2,%3,%4};" ::"r"(addr), "f"(a), "f"(b), "f"(c), "f"(d) : "memory");
}
__device__ __forceinline__ void lds128(float (&v)[4], uint32_t addr) {
  asm volatile("ld.shared.v4.f32 {%0,%1,%2,%3}, [%4];" : "=f"(v[0]), "=f"(v[1]), "=f"(v[2]), "=f"(v[3]) : "r"(addr) : "memory");
}
__device__ __forceinline__ void lds128u(uint32_t (&v)[4], uint32_t addr) {
  asm volatile("ld.shared.v4.u32 {%0,%1,%2,%3}, [%4];" : "=r"(v[0]), "=r"(v[1]), "=r"(v[2]), "=r"(v[3]) : "r"(addr) : "memory");
}
__device__ __forceinline__ void sts128u(uint32_t addr, const uint32_t (&v)[4]) {
  asm volatile("st.shared.v4.u32 [%0], {%1,%2,%3,%4};" ::"r"(addr), "r"(v[0]), "r"(v[1]), "r"(v[2]), "r"(v[3]) : "memory");
}
__device__ __forceinline__ void mbar_arrive_remote(uint32_t b) {
  asm volatile("mbarrier.arrive.shared::cluster.b64 _, [%0];" ::"r"(b) : "memory");
}
__device__ __forceinline__ void mma8(float (&c)[4], uint32_t a0, uint32_t a1, uint32_t b0) {
  asm("mma.sync.aligned.m16n8k8.row.col.f32.bf16.bf16.f32 {%0,%1,%2,%3},{%4,%5},{%6},{%0,%1,%2,%3};"
      : "+f"(c[0]), "+f"(c[1]), "+f"(c[2]), "+f"(c[3]) : "r"(a0), "r"(a1), "r"(b0));
}
__device__ __forceinline__ uint32_t pack_bf16(float lo, float hi) {
  uint32_t r; asm("cvt.rn.bf16x2.f32 %0, %1, %2;" : "=r"(r) : "f"(hi), "f"(lo)); return r;
}
__device__ __forceinline__ uint32_t transpose8(uint32_t v) {
  uint32_t d; asm volatile("movmatrix.sync.aligned.m8n8.trans.b16 %0, %1;" : "=r"(d) : "r"(v)); return d;
}
__device__ __forceinline__ float ex2f(float x) { float y; asm("ex2.approx.ftz.f32 %0, %1;" : "=f"(y) : "f"(x)); return y; }
__device__ __forceinline__ float rcpf(float x) { float y; asm("rcp.approx.ftz.f32 %0, %1;" : "=f"(y) : "f"(x)); return y; }
template <int LUT> __device__ __forceinline__ uint32_t lop3(uint32_t a, uint32_t b, uint32_t c) {
  uint32_t d; asm("lop3.b32 %0,%1,%2,%3,%4;" : "=r"(d) : "r"(a), "r"(b), "r"(c), "n"(LUT)); return d;
}
__device__ __forceinline__ void wg_fence() { asm volatile("wgmma.fence.sync.aligned;" ::: "memory"); }
__device__ __forceinline__ void wg_commit() { asm volatile("wgmma.commit_group.sync.aligned;" ::: "memory"); }
template <int N> __device__ __forceinline__ void wg_wait() { asm volatile("wgmma.wait_group.sync.aligned %0;" ::"n"(N) : "memory"); }
__device__ __forceinline__ void fence_async_smem() { asm volatile("fence.proxy.async.shared::cta;" ::: "memory"); }
__device__ __forceinline__ uint64_t make_desc(uint32_t addr, uint32_t lbo, uint32_t sbo, uint32_t swz) {
  return (uint64_t)((addr >> 4) & 0x3FFF) | ((uint64_t)(lbo >> 4) << 16) | ((uint64_t)(sbo >> 4) << 32) | ((uint64_t)swz << 62);
}
__device__ __forceinline__ void tma2d(uint32_t dst, const CUtensorMap* m, int c0, int c1, uint32_t bar) {
  asm volatile("cp.async.bulk.tensor.2d.shared::cluster.global.mbarrier::complete_tx::bytes [%0], [%1, {%3, %4}], [%2];"
               ::"r"(dst), "l"(m), "r"(bar), "r"(c0), "r"(c1) : "memory");
}
__device__ __forceinline__ uint32_t clk32() { uint32_t c; asm volatile("mov.u32 %0, %%clock;" : "=r"(c)::"memory"); return c; }
template <int O> __device__ __forceinline__ void wg_ss224(float (&d)[112], uint64_t da, uint64_t db, int acc) {
  asm volatile("{\n .reg .pred p;\n setp.ne.b32 p, %114, 0;\n"
      "wgmma.mma_async.sync.aligned.m64n224k16.f32.bf16.bf16 {%0,%1,%2,%3,%4,%5,%6,%7,%8,%9,%10,%11,%12,%13,%14,%15,%16,%17,%18,%19,%20,%21,%22,%23,%24,%25,%26,%27,%28,%29,%30,%31,%32,%33,%34,%35,%36,%37,%38,%39,%40,%41,%42,%43,%44,%45,%46,%47,%48,%49,%50,%51,%52,%53,%54,%55,%56,%57,%58,%59,%60,%61,%62,%63,%64,%65,%66,%67,%68,%69,%70,%71,%72,%73,%74,%75,%76,%77,%78,%79,%80,%81,%82,%83,%84,%85,%86,%87,%88,%89,%90,%91,%92,%93,%94,%95,%96,%97,%98,%99,%100,%101,%102,%103,%104,%105,%106,%107,%108,%109,%110,%111}, %112, %113, p, 1, 1, 0, 0;\n}"
      : "+f"(d[O + 0]), "+f"(d[O + 1]), "+f"(d[O + 2]), "+f"(d[O + 3]), "+f"(d[O + 4]), "+f"(d[O + 5]), "+f"(d[O + 6]), "+f"(d[O + 7]),
        "+f"(d[O + 8]), "+f"(d[O + 9]), "+f"(d[O + 10]), "+f"(d[O + 11]), "+f"(d[O + 12]), "+f"(d[O + 13]), "+f"(d[O + 14]), "+f"(d[O + 15]),
        "+f"(d[O + 16]), "+f"(d[O + 17]), "+f"(d[O + 18]), "+f"(d[O + 19]), "+f"(d[O + 20]), "+f"(d[O + 21]), "+f"(d[O + 22]), "+f"(d[O + 23]),
        "+f"(d[O + 24]), "+f"(d[O + 25]), "+f"(d[O + 26]), "+f"(d[O + 27]), "+f"(d[O + 28]), "+f"(d[O + 29]), "+f"(d[O + 30]), "+f"(d[O + 31]),
        "+f"(d[O + 32]), "+f"(d[O + 33]), "+f"(d[O + 34]), "+f"(d[O + 35]), "+f"(d[O + 36]), "+f"(d[O + 37]), "+f"(d[O + 38]), "+f"(d[O + 39]),
        "+f"(d[O + 40]), "+f"(d[O + 41]), "+f"(d[O + 42]), "+f"(d[O + 43]), "+f"(d[O + 44]), "+f"(d[O + 45]), "+f"(d[O + 46]), "+f"(d[O + 47]),
        "+f"(d[O + 48]), "+f"(d[O + 49]), "+f"(d[O + 50]), "+f"(d[O + 51]), "+f"(d[O + 52]), "+f"(d[O + 53]), "+f"(d[O + 54]), "+f"(d[O + 55]),
        "+f"(d[O + 56]), "+f"(d[O + 57]), "+f"(d[O + 58]), "+f"(d[O + 59]), "+f"(d[O + 60]), "+f"(d[O + 61]), "+f"(d[O + 62]), "+f"(d[O + 63]),
        "+f"(d[O + 64]), "+f"(d[O + 65]), "+f"(d[O + 66]), "+f"(d[O + 67]), "+f"(d[O + 68]), "+f"(d[O + 69]), "+f"(d[O + 70]), "+f"(d[O + 71]),
        "+f"(d[O + 72]), "+f"(d[O + 73]), "+f"(d[O + 74]), "+f"(d[O + 75]), "+f"(d[O + 76]), "+f"(d[O + 77]), "+f"(d[O + 78]), "+f"(d[O + 79]),
        "+f"(d[O + 80]), "+f"(d[O + 81]), "+f"(d[O + 82]), "+f"(d[O + 83]), "+f"(d[O + 84]), "+f"(d[O + 85]), "+f"(d[O + 86]), "+f"(d[O + 87]),
        "+f"(d[O + 88]), "+f"(d[O + 89]), "+f"(d[O + 90]), "+f"(d[O + 91]), "+f"(d[O + 92]), "+f"(d[O + 93]), "+f"(d[O + 94]), "+f"(d[O + 95]),
        "+f"(d[O + 96]), "+f"(d[O + 97]), "+f"(d[O + 98]), "+f"(d[O + 99]), "+f"(d[O + 100]), "+f"(d[O + 101]), "+f"(d[O + 102]), "+f"(d[O + 103]),
        "+f"(d[O + 104]), "+f"(d[O + 105]), "+f"(d[O + 106]), "+f"(d[O + 107]), "+f"(d[O + 108]), "+f"(d[O + 109]), "+f"(d[O + 110]), "+f"(d[O + 111])
      : "l"(da), "l"(db), "r"(acc));
}
template <int O> __device__ __forceinline__ void wg_ss256t(float (&d)[128], uint64_t da, uint64_t db, int acc) {
  asm volatile("{\n .reg .pred p;\n setp.ne.b32 p, %130, 0;\n"
      "wgmma.mma_async.sync.aligned.m64n256k16.f32.bf16.bf16 {%0,%1,%2,%3,%4,%5,%6,%7,%8,%9,%10,%11,%12,%13,%14,%15,%16,%17,%18,%19,%20,%21,%22,%23,%24,%25,%26,%27,%28,%29,%30,%31,%32,%33,%34,%35,%36,%37,%38,%39,%40,%41,%42,%43,%44,%45,%46,%47,%48,%49,%50,%51,%52,%53,%54,%55,%56,%57,%58,%59,%60,%61,%62,%63,%64,%65,%66,%67,%68,%69,%70,%71,%72,%73,%74,%75,%76,%77,%78,%79,%80,%81,%82,%83,%84,%85,%86,%87,%88,%89,%90,%91,%92,%93,%94,%95,%96,%97,%98,%99,%100,%101,%102,%103,%104,%105,%106,%107,%108,%109,%110,%111,%112,%113,%114,%115,%116,%117,%118,%119,%120,%121,%122,%123,%124,%125,%126,%127}, %128, %129, p, 1, 1, 0, 1;\n}"
      : "+f"(d[O + 0]), "+f"(d[O + 1]), "+f"(d[O + 2]), "+f"(d[O + 3]), "+f"(d[O + 4]), "+f"(d[O + 5]), "+f"(d[O + 6]), "+f"(d[O + 7]),
        "+f"(d[O + 8]), "+f"(d[O + 9]), "+f"(d[O + 10]), "+f"(d[O + 11]), "+f"(d[O + 12]), "+f"(d[O + 13]), "+f"(d[O + 14]), "+f"(d[O + 15]),
        "+f"(d[O + 16]), "+f"(d[O + 17]), "+f"(d[O + 18]), "+f"(d[O + 19]), "+f"(d[O + 20]), "+f"(d[O + 21]), "+f"(d[O + 22]), "+f"(d[O + 23]),
        "+f"(d[O + 24]), "+f"(d[O + 25]), "+f"(d[O + 26]), "+f"(d[O + 27]), "+f"(d[O + 28]), "+f"(d[O + 29]), "+f"(d[O + 30]), "+f"(d[O + 31]),
        "+f"(d[O + 32]), "+f"(d[O + 33]), "+f"(d[O + 34]), "+f"(d[O + 35]), "+f"(d[O + 36]), "+f"(d[O + 37]), "+f"(d[O + 38]), "+f"(d[O + 39]),
        "+f"(d[O + 40]), "+f"(d[O + 41]), "+f"(d[O + 42]), "+f"(d[O + 43]), "+f"(d[O + 44]), "+f"(d[O + 45]), "+f"(d[O + 46]), "+f"(d[O + 47]),
        "+f"(d[O + 48]), "+f"(d[O + 49]), "+f"(d[O + 50]), "+f"(d[O + 51]), "+f"(d[O + 52]), "+f"(d[O + 53]), "+f"(d[O + 54]), "+f"(d[O + 55]),
        "+f"(d[O + 56]), "+f"(d[O + 57]), "+f"(d[O + 58]), "+f"(d[O + 59]), "+f"(d[O + 60]), "+f"(d[O + 61]), "+f"(d[O + 62]), "+f"(d[O + 63]),
        "+f"(d[O + 64]), "+f"(d[O + 65]), "+f"(d[O + 66]), "+f"(d[O + 67]), "+f"(d[O + 68]), "+f"(d[O + 69]), "+f"(d[O + 70]), "+f"(d[O + 71]),
        "+f"(d[O + 72]), "+f"(d[O + 73]), "+f"(d[O + 74]), "+f"(d[O + 75]), "+f"(d[O + 76]), "+f"(d[O + 77]), "+f"(d[O + 78]), "+f"(d[O + 79]),
        "+f"(d[O + 80]), "+f"(d[O + 81]), "+f"(d[O + 82]), "+f"(d[O + 83]), "+f"(d[O + 84]), "+f"(d[O + 85]), "+f"(d[O + 86]), "+f"(d[O + 87]),
        "+f"(d[O + 88]), "+f"(d[O + 89]), "+f"(d[O + 90]), "+f"(d[O + 91]), "+f"(d[O + 92]), "+f"(d[O + 93]), "+f"(d[O + 94]), "+f"(d[O + 95]),
        "+f"(d[O + 96]), "+f"(d[O + 97]), "+f"(d[O + 98]), "+f"(d[O + 99]), "+f"(d[O + 100]), "+f"(d[O + 101]), "+f"(d[O + 102]), "+f"(d[O + 103]),
        "+f"(d[O + 104]), "+f"(d[O + 105]), "+f"(d[O + 106]), "+f"(d[O + 107]), "+f"(d[O + 108]), "+f"(d[O + 109]), "+f"(d[O + 110]), "+f"(d[O + 111]),
        "+f"(d[O + 112]), "+f"(d[O + 113]), "+f"(d[O + 114]), "+f"(d[O + 115]), "+f"(d[O + 116]), "+f"(d[O + 117]), "+f"(d[O + 118]), "+f"(d[O + 119]),
        "+f"(d[O + 120]), "+f"(d[O + 121]), "+f"(d[O + 122]), "+f"(d[O + 123]), "+f"(d[O + 124]), "+f"(d[O + 125]), "+f"(d[O + 126]), "+f"(d[O + 127])
      : "l"(da), "l"(db), "r"(acc));
}
template <int O> __device__ __forceinline__ void wg_ss192t(float (&d)[96], uint64_t da, uint64_t db, int acc) {
  asm volatile("{\n .reg .pred p;\n setp.ne.b32 p, %98, 0;\n"
      "wgmma.mma_async.sync.aligned.m64n192k16.f32.bf16.bf16 {%0,%1,%2,%3,%4,%5,%6,%7,%8,%9,%10,%11,%12,%13,%14,%15,%16,%17,%18,%19,%20,%21,%22,%23,%24,%25,%26,%27,%28,%29,%30,%31,%32,%33,%34,%35,%36,%37,%38,%39,%40,%41,%42,%43,%44,%45,%46,%47,%48,%49,%50,%51,%52,%53,%54,%55,%56,%57,%58,%59,%60,%61,%62,%63,%64,%65,%66,%67,%68,%69,%70,%71,%72,%73,%74,%75,%76,%77,%78,%79,%80,%81,%82,%83,%84,%85,%86,%87,%88,%89,%90,%91,%92,%93,%94,%95}, %96, %97, p, 1, 1, 0, 1;\n}"
      : "+f"(d[O + 0]), "+f"(d[O + 1]), "+f"(d[O + 2]), "+f"(d[O + 3]), "+f"(d[O + 4]), "+f"(d[O + 5]), "+f"(d[O + 6]), "+f"(d[O + 7]),
        "+f"(d[O + 8]), "+f"(d[O + 9]), "+f"(d[O + 10]), "+f"(d[O + 11]), "+f"(d[O + 12]), "+f"(d[O + 13]), "+f"(d[O + 14]), "+f"(d[O + 15]),
        "+f"(d[O + 16]), "+f"(d[O + 17]), "+f"(d[O + 18]), "+f"(d[O + 19]), "+f"(d[O + 20]), "+f"(d[O + 21]), "+f"(d[O + 22]), "+f"(d[O + 23]),
        "+f"(d[O + 24]), "+f"(d[O + 25]), "+f"(d[O + 26]), "+f"(d[O + 27]), "+f"(d[O + 28]), "+f"(d[O + 29]), "+f"(d[O + 30]), "+f"(d[O + 31]),
        "+f"(d[O + 32]), "+f"(d[O + 33]), "+f"(d[O + 34]), "+f"(d[O + 35]), "+f"(d[O + 36]), "+f"(d[O + 37]), "+f"(d[O + 38]), "+f"(d[O + 39]),
        "+f"(d[O + 40]), "+f"(d[O + 41]), "+f"(d[O + 42]), "+f"(d[O + 43]), "+f"(d[O + 44]), "+f"(d[O + 45]), "+f"(d[O + 46]), "+f"(d[O + 47]),
        "+f"(d[O + 48]), "+f"(d[O + 49]), "+f"(d[O + 50]), "+f"(d[O + 51]), "+f"(d[O + 52]), "+f"(d[O + 53]), "+f"(d[O + 54]), "+f"(d[O + 55]),
        "+f"(d[O + 56]), "+f"(d[O + 57]), "+f"(d[O + 58]), "+f"(d[O + 59]), "+f"(d[O + 60]), "+f"(d[O + 61]), "+f"(d[O + 62]), "+f"(d[O + 63]),
        "+f"(d[O + 64]), "+f"(d[O + 65]), "+f"(d[O + 66]), "+f"(d[O + 67]), "+f"(d[O + 68]), "+f"(d[O + 69]), "+f"(d[O + 70]), "+f"(d[O + 71]),
        "+f"(d[O + 72]), "+f"(d[O + 73]), "+f"(d[O + 74]), "+f"(d[O + 75]), "+f"(d[O + 76]), "+f"(d[O + 77]), "+f"(d[O + 78]), "+f"(d[O + 79]),
        "+f"(d[O + 80]), "+f"(d[O + 81]), "+f"(d[O + 82]), "+f"(d[O + 83]), "+f"(d[O + 84]), "+f"(d[O + 85]), "+f"(d[O + 86]), "+f"(d[O + 87]),
        "+f"(d[O + 88]), "+f"(d[O + 89]), "+f"(d[O + 90]), "+f"(d[O + 91]), "+f"(d[O + 92]), "+f"(d[O + 93]), "+f"(d[O + 94]), "+f"(d[O + 95])
      : "l"(da), "l"(db), "r"(acc));
}
template <int O> __device__ __forceinline__ void wg_ss32(float (&d)[64], uint64_t da, uint64_t db, int acc) {
  asm volatile("{\n .reg .pred p;\n setp.ne.b32 p, %18, 0;\n"
      "wgmma.mma_async.sync.aligned.m64n32k16.f32.bf16.bf16 {%0,%1,%2,%3,%4,%5,%6,%7,%8,%9,%10,%11,%12,%13,%14,%15}, %16, %17, p, 1, 1, 0, 0;\n}"
      : "+f"(d[O + 0]), "+f"(d[O + 1]), "+f"(d[O + 2]), "+f"(d[O + 3]), "+f"(d[O + 4]), "+f"(d[O + 5]), "+f"(d[O + 6]), "+f"(d[O + 7]),
        "+f"(d[O + 8]), "+f"(d[O + 9]), "+f"(d[O + 10]), "+f"(d[O + 11]), "+f"(d[O + 12]), "+f"(d[O + 13]), "+f"(d[O + 14]), "+f"(d[O + 15])
      : "l"(da), "l"(db), "r"(acc));
}
template <int O> __device__ __forceinline__ void wg_ss112(float (&d)[56], uint64_t da, uint64_t db, int acc) {
  asm volatile("{\n .reg .pred p;\n setp.ne.b32 p, %58, 0;\n"
      "wgmma.mma_async.sync.aligned.m64n112k16.f32.bf16.bf16 {%0,%1,%2,%3,%4,%5,%6,%7,%8,%9,%10,%11,%12,%13,%14,%15,%16,%17,%18,%19,%20,%21,%22,%23,%24,%25,%26,%27,%28,%29,%30,%31,%32,%33,%34,%35,%36,%37,%38,%39,%40,%41,%42,%43,%44,%45,%46,%47,%48,%49,%50,%51,%52,%53,%54,%55}, %56, %57, p, 1, 1, 0, 0;\n}"
      : "+f"(d[O + 0]), "+f"(d[O + 1]), "+f"(d[O + 2]), "+f"(d[O + 3]), "+f"(d[O + 4]), "+f"(d[O + 5]), "+f"(d[O + 6]), "+f"(d[O + 7]),
        "+f"(d[O + 8]), "+f"(d[O + 9]), "+f"(d[O + 10]), "+f"(d[O + 11]), "+f"(d[O + 12]), "+f"(d[O + 13]), "+f"(d[O + 14]), "+f"(d[O + 15]),
        "+f"(d[O + 16]), "+f"(d[O + 17]), "+f"(d[O + 18]), "+f"(d[O + 19]), "+f"(d[O + 20]), "+f"(d[O + 21]), "+f"(d[O + 22]), "+f"(d[O + 23]),
        "+f"(d[O + 24]), "+f"(d[O + 25]), "+f"(d[O + 26]), "+f"(d[O + 27]), "+f"(d[O + 28]), "+f"(d[O + 29]), "+f"(d[O + 30]), "+f"(d[O + 31]),
        "+f"(d[O + 32]), "+f"(d[O + 33]), "+f"(d[O + 34]), "+f"(d[O + 35]), "+f"(d[O + 36]), "+f"(d[O + 37]), "+f"(d[O + 38]), "+f"(d[O + 39]),
        "+f"(d[O + 40]), "+f"(d[O + 41]), "+f"(d[O + 42]), "+f"(d[O + 43]), "+f"(d[O + 44]), "+f"(d[O + 45]), "+f"(d[O + 46]), "+f"(d[O + 47]),
        "+f"(d[O + 48]), "+f"(d[O + 49]), "+f"(d[O + 50]), "+f"(d[O + 51]), "+f"(d[O + 52]), "+f"(d[O + 53]), "+f"(d[O + 54]), "+f"(d[O + 55])
      : "l"(da), "l"(db), "r"(acc));
}
__device__ __forceinline__ void wg_rs112(float (&d)[56], uint32_t a0, uint32_t a1, uint32_t a2, uint32_t a3, uint64_t db, int acc) {
  asm volatile("{\n .reg .pred p;\n setp.ne.b32 p, %61, 0;\n"
      "wgmma.mma_async.sync.aligned.m64n112k16.f32.bf16.bf16 {%0,%1,%2,%3,%4,%5,%6,%7,%8,%9,%10,%11,%12,%13,%14,%15,%16,%17,%18,%19,%20,%21,%22,%23,%24,%25,%26,%27,%28,%29,%30,%31,%32,%33,%34,%35,%36,%37,%38,%39,%40,%41,%42,%43,%44,%45,%46,%47,%48,%49,%50,%51,%52,%53,%54,%55}, {%56,%57,%58,%59}, %60, p, 1, 1, 0;\n}"
      : "+f"(d[0]), "+f"(d[1]), "+f"(d[2]), "+f"(d[3]), "+f"(d[4]), "+f"(d[5]), "+f"(d[6]), "+f"(d[7]),
        "+f"(d[8]), "+f"(d[9]), "+f"(d[10]), "+f"(d[11]), "+f"(d[12]), "+f"(d[13]), "+f"(d[14]), "+f"(d[15]),
        "+f"(d[16]), "+f"(d[17]), "+f"(d[18]), "+f"(d[19]), "+f"(d[20]), "+f"(d[21]), "+f"(d[22]), "+f"(d[23]),
        "+f"(d[24]), "+f"(d[25]), "+f"(d[26]), "+f"(d[27]), "+f"(d[28]), "+f"(d[29]), "+f"(d[30]), "+f"(d[31]),
        "+f"(d[32]), "+f"(d[33]), "+f"(d[34]), "+f"(d[35]), "+f"(d[36]), "+f"(d[37]), "+f"(d[38]), "+f"(d[39]),
        "+f"(d[40]), "+f"(d[41]), "+f"(d[42]), "+f"(d[43]), "+f"(d[44]), "+f"(d[45]), "+f"(d[46]), "+f"(d[47]),
        "+f"(d[48]), "+f"(d[49]), "+f"(d[50]), "+f"(d[51]), "+f"(d[52]), "+f"(d[53]), "+f"(d[54]), "+f"(d[55])
      : "r"(a0), "r"(a1), "r"(a2), "r"(a3), "l"(db), "r"(acc));
}
__device__ __forceinline__ void wg_rs64(float (&d)[32], uint32_t a0, uint32_t a1, uint32_t a2, uint32_t a3, uint64_t db, int acc) {
  asm volatile("{\n .reg .pred p;\n setp.ne.b32 p, %37, 0;\n"
      "wgmma.mma_async.sync.aligned.m64n64k16.f32.bf16.bf16 {%0,%1,%2,%3,%4,%5,%6,%7,%8,%9,%10,%11,%12,%13,%14,%15,%16,%17,%18,%19,%20,%21,%22,%23,%24,%25,%26,%27,%28,%29,%30,%31}, {%32,%33,%34,%35}, %36, p, 1, 1, 0;\n}"
      : "+f"(d[0]), "+f"(d[1]), "+f"(d[2]), "+f"(d[3]), "+f"(d[4]), "+f"(d[5]), "+f"(d[6]), "+f"(d[7]),
        "+f"(d[8]), "+f"(d[9]), "+f"(d[10]), "+f"(d[11]), "+f"(d[12]), "+f"(d[13]), "+f"(d[14]), "+f"(d[15]),
        "+f"(d[16]), "+f"(d[17]), "+f"(d[18]), "+f"(d[19]), "+f"(d[20]), "+f"(d[21]), "+f"(d[22]), "+f"(d[23]),
        "+f"(d[24]), "+f"(d[25]), "+f"(d[26]), "+f"(d[27]), "+f"(d[28]), "+f"(d[29]), "+f"(d[30]), "+f"(d[31])
      : "r"(a0), "r"(a1), "r"(a2), "r"(a3), "l"(db), "r"(acc));
}
__device__ __forceinline__ void wg_rs16t(float (&d)[8], uint32_t a0, uint32_t a1, uint32_t a2, uint32_t a3, uint64_t db, int acc) {
  asm volatile("{\n .reg .pred p;\n setp.ne.b32 p, %13, 0;\n"
      "wgmma.mma_async.sync.aligned.m64n16k16.f32.bf16.bf16 {%0,%1,%2,%3,%4,%5,%6,%7}, {%8,%9,%10,%11}, %12, p, 1, 1, 1;\n}"
      : "+f"(d[0]), "+f"(d[1]), "+f"(d[2]), "+f"(d[3]), "+f"(d[4]), "+f"(d[5]), "+f"(d[6]), "+f"(d[7])
      : "r"(a0), "r"(a1), "r"(a2), "r"(a3), "l"(db), "r"(acc));
}
constexpr int GSLOT = 112 * 1024;
__device__ __align__(1024) uint32_t g_xc[16 * 56 * 16 * 32];
__device__ __align__(1024) uint32_t g_xq[NSEG * 56 * 4 * 32];
__device__ __align__(1024) uint32_t g_A[NH * 2 * 56 * 28 * 32];
__device__ __align__(1024) uint32_t g_B[NH * 2 * 56 * 28 * 32];
__device__ __align__(1024) uint32_t g_Vt[NSEG * 80 * 56 * 32];
__device__ __align__(1024) uint32_t g_P[NSEG * 80 * 4 * 32];
__device__ __align__(1024) uint32_t g_mem[NSEG * DM * 4];
__device__ __align__(1024) uint32_t g_H[16 * 224 * 16 * 32];
__device__ __align__(1024) uint32_t g_G[NSEG * 4 * 56 * 32];
__device__ __align__(1024) uint32_t g_xch[2 * GSLOT / 4];
enum { F_LN = 0, F_B = 32, F_A = 64, F_P = 96, F_H = 128, F_G = 160, F_M = 176, F_C = 192, F_U = 256, F_DONE = 512, F_COUNT = 544 };
__device__ __align__(128) unsigned g_flag[F_COUNT];

__device__ __forceinline__ void bulk_store(void* g, uint32_t sm, uint32_t bytes) {
  asm volatile("cp.async.bulk.global.shared::cta.bulk_group [%0], [%1], %2;" ::"l"(g), "r"(sm), "r"(bytes) : "memory");
}
__device__ __forceinline__ void bulk_load(uint32_t dst, const void* g, uint32_t bytes, uint32_t bar) {
  asm volatile("cp.async.bulk.shared::cluster.global.mbarrier::complete_tx::bytes [%0], [%1], %2, [%3];"
               ::"r"(dst), "l"(g), "r"(bytes), "r"(bar) : "memory");
}
__device__ __forceinline__ uint64_t policy_evict_first() {
  uint64_t p; asm("createpolicy.fractional.L2::evict_first.b64 %0, 1.0;" : "=l"(p)); return p;
}
__device__ __forceinline__ void bulk_load_last(uint32_t dst, const void* g, uint32_t bytes, uint32_t bar) {
  asm volatile("cp.async.bulk.shared::cluster.global.mbarrier::complete_tx::bytes.L2::cache_hint [%0], [%1], %2, [%3], %4;"
               ::"r"(dst), "l"(g), "r"(bytes), "r"(bar), "l"(policy_evict_first()) : "memory");
}
__device__ __forceinline__ void bulk_load_mc(uint32_t dst, const void* g, uint32_t bytes, uint32_t bar, uint16_t mask) {
  asm volatile("cp.async.bulk.shared::cluster.global.mbarrier::complete_tx::bytes.multicast::cluster [%0], [%1], %2, [%3], %4;"
               ::"r"(dst), "l"(g), "r"(bytes), "r"(bar), "h"(mask) : "memory");
}
__device__ __forceinline__ void tma2d_mc(uint32_t dst, const CUtensorMap* m, int c0, int c1, uint32_t bar, uint16_t mask) {
  asm volatile("cp.async.bulk.tensor.2d.shared::cluster.global.mbarrier::complete_tx::bytes.multicast::cluster [%0], [%1, {%3, %4}], [%2], %5;"
               ::"r"(dst), "l"(m), "r"(bar), "r"(c0), "r"(c1), "h"(mask) : "memory");
}
__device__ __forceinline__ void tma2d_store(const CUtensorMap* m, int c0, int c1, uint32_t src) {
  asm volatile("cp.async.bulk.tensor.2d.global.shared::cta.bulk_group [%0, {%2, %3}], [%1];" ::"l"(m), "r"(src), "r"(c0), "r"(c1) : "memory");
}
__device__ __forceinline__ void bulk_commit() { asm volatile("cp.async.bulk.commit_group;" ::: "memory"); }
__device__ __forceinline__ void bulk_wait_all() { asm volatile("cp.async.bulk.wait_group 0;" ::: "memory"); }
__device__ __forceinline__ void bulk_wait_read() { asm volatile("cp.async.bulk.wait_group.read 0;" ::: "memory"); }
__device__ __forceinline__ void flag_add(int f) { asm volatile("red.relaxed.gpu.global.add.u32 [%0], 1;" ::"l"(&g_flag[f]) : "memory"); }
__device__ __forceinline__ void fence_gpu() { asm volatile("fence.acq_rel.gpu;" ::: "memory"); }
__device__ __forceinline__ void wait_flags(int f, int n, unsigned target, uint32_t limit = POLL_LIMIT) {
  const unsigned* p = &g_flag[f + min((int)(threadIdx.x & 31), n - 1)];
#pragma unroll 1
  for (uint32_t it = 0; it < limit; it++) {
    unsigned v;
    asm volatile("ld.relaxed.gpu.global.u32 %0, [%1];" : "=r"(v) : "l"(p) : "memory");
    if (__all_sync(0xffffffffu, v >= target)) break;
    __nanosleep(20);
  }
  asm volatile("fence.proxy.async.global;" ::: "memory");
}
__device__ __forceinline__ float bf_round(float x) { return __uint_as_float(pack_bf16(0.f, x) & 0xFFFF0000u); }
__device__ __forceinline__ float bf_lo(uint32_t v) { return __uint_as_float(v << 16); }
__device__ __forceinline__ float bf_hi(uint32_t v) { return __uint_as_float(v & 0xFFFF0000u); }
__device__ __forceinline__ float silu(float x) { return x * rcpf(1.f + ex2f(-1.4426950408889634f * x)); }
constexpr int NSH = 4;
#define NSX 4
constexpr int NPAR = 14 - NSH - NSX;
constexpr int NOWN = 13;
constexpr int C_BAR = 0, C_AG = 0, C_SB = 64, C_XB = 72, C_ZERO = 128, C_PF = 136, C_PE = 176, C_AF = 216, C_AE = 248;
constexpr int C_MEM = 1024, C_T = 15360, C_S = 18944, C_V = 21504, C_VP = 25088, C_W = 28672, C_B = 31744;
constexpr int C_B2 = C_B + 6 * (14 - NSH) * 512;
constexpr int P_ST = 67584, P_A = 93184, P_R = P_A + 65536, P_NS = 5, C_X = P_A, XBUF = 14336;
constexpr int NRE = 5, C_A1 = P_R;
constexpr int NPARK = 5, P_PARK = 8192;
constexpr int C_SMEM = P_R + P_NS * 14336 + 1024;
static_assert(C_B2 + 8 * (14 - NOWN) * 512 <= P_ST, "layout");
constexpr uint32_t BF_ONE2 = 0x3F803F80u;
struct ChainMaps { CUtensorMap wq, wk, wv, wo, ga, gb; };
#define PT(i)
#define PROF(i)
#define PROFM(i)

__device__ __forceinline__ void st_async32(uint32_t dst, uint32_t v, uint32_t bar) {
  asm volatile("st.async.shared::cluster.mbarrier::complete_tx::bytes.b32 [%0], %1, [%2];" ::"r"(dst), "r"(v), "r"(bar) : "memory");
}
__device__ __forceinline__ void st_async128(uint32_t dst, uint32_t a, uint32_t b, uint32_t c, uint32_t d, uint32_t bar) {
  asm volatile("st.async.shared::cluster.mbarrier::complete_tx::bytes.v4.b32 [%0], {%1,%2,%3,%4}, [%5];"
               ::"r"(dst), "r"(a), "r"(b), "r"(c), "r"(d), "r"(bar) : "memory");
}
__device__ __forceinline__ void stg_relaxed(void* p, uint32_t v) { asm volatile("st.relaxed.gpu.global.u32 [%0], %1;" ::"l"(p), "r"(v) : "memory"); }
__device__ __forceinline__ uint4 ldg_relaxed16(const void* p) {
  uint4 v; asm volatile("ld.relaxed.gpu.global.v4.u32 {%0,%1,%2,%3}, [%4];" : "=r"(v.x), "=r"(v.y), "=r"(v.z), "=r"(v.w) : "l"(p) : "memory"); return v;
}

__device__ __forceinline__ uint32_t opaque(uint32_t v) { return __shfl_sync(0xffffffffu, v, threadIdx.x & 31); }
template <typename T> __device__ __forceinline__ T* opaque_ptr(T* p) {
  const uint64_t v = reinterpret_cast<uint64_t>(p);
  return reinterpret_cast<T*>((uint64_t)opaque((uint32_t)v) | ((uint64_t)opaque((uint32_t)(v >> 32)) << 32));
}

__device__ __forceinline__ void ld_quarter(uint32_t (&b)[14], uint32_t ad) {
  ldsm4t(b[0], b[1], b[2], b[3], ad);
  ldsm4t(b[4], b[5], b[6], b[7], ad + 512);
  ldsm4t(b[8], b[9], b[10], b[11], ad + 1024);
  ldsm2t(b[12], b[13], ad + 1536);
}
__device__ __forceinline__ void load_seg(uint32_t sb, int buf, int seg, int h, int j) {
  if ((seg & 3) == 0) wait_flags(F_U + (seg >> 2) * 16 + h, 1, 2);
  const uint32_t bar = sb + C_XB + buf * 8, dst = sb + C_X + buf * XBUF;
  if (elect_one()) {
    mbar_expect(bar, XBUF);
    bulk_load(dst, g_xq + (size_t)(seg * 56 + j * 14) * 128, 7168, bar);
#pragma unroll 1
    for (int i = 0; i < 4; i++) bulk_load(dst + 7168 + i * 1792, g_Vt + (size_t)((seg * 80 + 4 * h + i) * 56 + j * 14) * 32, 1792, bar);
  }
  __syncwarp();
}
__device__ __forceinline__ void prefetch2d(const CUtensorMap* m, int c0, int c1) {
  asm volatile("cp.async.bulk.prefetch.tensor.2d.L2.global [%0, {%1, %2}];" ::"l"(m), "r"(c0), "r"(c1) : "memory");
}
__device__ __forceinline__ uint32_t tagged(float lo, float hi, uint32_t tag) {
  return lop3<0xD8>(pack_bf16(__uint_as_float(__float_as_uint(lo) + 0x8000u), hi), tag, 1u);
}
__device__ __forceinline__ uint32_t add_bf16x2(uint32_t a, uint32_t b) {
  uint32_t d; asm("add.rn.bf16x2 %0, %1, %2;" : "=r"(d) : "r"(a), "r"(b)); return d;
}
enum { B_T = 1, B_V = 2, B_VP = 3, B_PV = 4, B_INIT = 5, B_ST = 6, B_W = 7, B_SR = 8, B_S = 9 };
#define XE 3
#define POLL_DELAY 280

__global__ void __cluster_dims__(16, 1, 1) __launch_bounds__(384, 1)
chain_kernel(const __grid_constant__ ChainMaps maps, const __nv_bfloat16* __restrict__ mem0) {
  extern __shared__ uint8_t smem_raw[];
  const uint32_t sb = (smem_u32(smem_raw) + 1023) & ~1023u;
  const int tid = threadIdx.x < 128 ? threadIdx.x + 256 : threadIdx.x - 128;
  const int w = __shfl_sync(0xffffffffu, tid >> 5, 0), l = tid & 31;
  const int rank = blockIdx.x & 15, cl = blockIdx.x >> 4;
  const int a = rank >> 2, j = rank & 3, h = cl * 4 + a;
  const int g4 = l >> 2, c = l & 3;

  PT(0);
  asm volatile("griddepcontrol.launch_dependents;");
  if (w >= 8 && l == 0)
    asm volatile("prefetch.tensormap [%0];" ::"l"(w == 8 ? &maps.wo : (w == 9 ? &maps.wv : (w == 10 ? &maps.wq : &maps.wk))) : "memory");
  if (tid == 0) {
    for (int i = 0; i < 12; i++) mbar_init(sb + C_BAR + i * 8, i == 8 ? 4 : 1);
    for (int i = 0; i < P_NS; i++) { mbar_init(sb + C_PF + i * 8, 1); mbar_init(sb + C_PE + i * 8, 8); }
    for (int i = 0; i < 4; i++) { mbar_init(sb + C_AF + i * 8, 1); mbar_init(sb + C_AE + i * 8, 8); }
    mbar_expect(sb + C_SB, 1920);
    sts32(sb + C_ZERO, 0);
    asm volatile("fence.mbarrier_init.release.cluster;" ::: "memory");
  }
  __syncthreads();
  asm volatile("barrier.cluster.arrive.relaxed.aligned;\n barrier.cluster.wait.aligned;" ::: "memory");

  if (w >= 8) {
    asm volatile("setmaxnreg.dec.sync.aligned.u32 72;");
    const int lw = w - 8, gj = (a - j) & 3;
    if (lw == 0) {
      uint32_t st = 0, sp = 1;
#pragma unroll 1
      for (int n = 0; n < 32; n++) {
        const int e = n & 3;
        mbar_wait(sb + C_PE + st * 8, sp);
        if (elect_one()) {
          mbar_expect(sb + C_PF + st * 8, 14336);
          if (e == j) tma2d_mc(sb + P_R + st * 14336, n < 16 ? &maps.wv : &maps.wq, h * DH + e * 64, ((a - (n >> 2)) & 3) * 112, sb + C_PF + st * 8, (uint16_t)(0xF << (a * 4)));
        }
        if (++st == P_NS) { st = 0; sp ^= 1; }
      }
    } else if (lw == 3) {
      if (elect_one()) {
#pragma unroll 1
        for (int e = 0; e < 4; e++) {
          mbar_expect(sb + C_AF + e * 8, 16384);
          for (int b = 0; b < 2; b++) tma2d(sb + P_A + e * 16384 + b * 8192, &maps.wo, j * 112 + b * 64, h * DH + e * 64, sb + C_AF + e * 8);
        }
      }
      mbar_wait(sb + C_AE, 0);
      if (elect_one()) {
#pragma unroll 1
        for (int e = 0; e < 4; e++) {
          mbar_expect(sb + C_AF + e * 8, 16384);
          tma2d(sb + P_A + e * 16384, &maps.wk, h * DH + e * 64, j * 112, sb + C_AF + e * 8);
          prefetch2d(&maps.wq, h * DH + j * 64, ((a - e) & 3) * 112);
        }
      }
      mbar_wait(sb + C_AE + 8, 0);
      wait_flags(F_LN, 1, 1, GATE_LIMIT);
      load_seg(sb, 0, 0, h, j);
      load_seg(sb, 1, 1, h, j);
    } else if (lw == 2) {
#pragma unroll 2
      for (int d = l; d < DM; d += 32) {
        uint32_t v[4];
#pragma unroll
        for (int q = 0; q < 4; q++)
          v[q] = __bfloat16_as_ushort(mem0[2 * q * DM + d]) | ((uint32_t)__bfloat16_as_ushort(mem0[(2 * q + 1) * DM + d]) << 16);
        const int qd = d / 112;
        sts128u(sb + C_MEM + (((a - qd) & 3) * 112 + d - qd * 112) * 16, v);
      }
      __syncwarp();
      wait_flags(F_LN, 1, 1, GATE_LIMIT);
      bar_arrive(B_INIT, 288);
      if (l < 2) mbar_arrive(sb + C_AG + l * 8);
    } else if (lw == 1) {
      if (elect_one()) {
#pragma unroll 1
        for (int g = 1; g < 4; g++) prefetch2d(&maps.wv, h * DH + j * 64, ((a - g) & 3) * 112);
      }
#pragma unroll 1
      for (int n = 0; n < 8; n++) {
        bar_sync(B_ST, 288);
        if (elect_one()) {
          tma2d_store(n < 4 ? &maps.gb : &maps.ga, (j & 1) * 224, (h * 2 + (j >> 1)) * 56 + ((a - n) & 3) * 14, sb + P_ST);
          bulk_commit();
        }
        bulk_wait_read();
        __syncwarp();
        bar_arrive(B_SR, 288);
        if ((n & 3) == 3) {
          bulk_wait_all();
          __syncwarp();
          if (l == 0) flag_add((n < 4 ? F_B : F_A) + h);
          __syncwarp();
        }
      }
    }
    if (lw < 2) wait_flags(F_LN, 1, 1, GATE_LIMIT);
    const uint32_t speer0 = mapa(sb, a * 4 + ((j + 1) & 3)), speer1 = mapa(sb, a * 4 + ((j + 2) & 3)), speer2 = mapa(sb, a * 4 + ((j + 3) & 3));
    const int t0 = lw == 3 ? 5 : lw * 2;
    const uint32_t lane16 = opaque(sb + l * 16);
    const uint32_t so = opaque(C_S + lw * 1024 + j * (lw < 2 ? 256 : 128) + l * 4);
    const uint32_t fbase = opaque(lw < 2 ? sb + C_X + (l >> 4) * 512 + lw * 256 + (l & 15) * 16
                                         : sb + C_MEM + gj * 1792 + (l >> 4) * 128 + (l & 7) * 16);
    const uint32_t ubase = opaque(sb + C_X + 7168 + (l >> 4) * 1792 + t0 * 256 + (l & 15) * 16);
    const uint32_t idm = opaque((2 * c == g4 ? 0x3F80u : 0u) | (2 * c + 1 == g4 ? 0x3F800000u : 0u));
    const uint32_t sel = opaque((g4 & 1) ? 0x3F800000u : 0x00003F80u);
    const int grow = j * 112 + t0 * 16 + g4;
    const uint32_t gwo = opaque((grow >> 2) * 1024 + cl * 256 + ((grow >> 1) & 1) * 128 + a * 32 + (grow & 1) * 16 + c * 4);
    const bool pact = (lw * 8 + g4) < 28;
    const int prl = pact ? lw * 8 + g4 : 24 + (g4 & 3), prow = rank * 28 + prl;
    const uint32_t gro = opaque((prow >> 2) * 1024 + ((prow >> 1) & 1) * 128 + c * 32 + (prow & 1) * 16);
    const uint32_t cpeer = opaque(mapa(sb, c) - mapa(sb, 0));
    const uint32_t ago = opaque((j * 28 + prl) * 16);
    int xi = 0;
    uint32_t xph = 0, par = 0, ph = 0;
    for (int s = 0; s < NSEG - 1; s++) {
      const uint32_t tag = ph ^ 1;
      const uint32_t xo = xi * XBUF;
      mbar_wait(sb + C_XB + xi * 8, xph);
      if (xi == 2) { xi = 0; xph ^= 1; } else xi++;
      auto scores = [&](auto two, const uint32_t (&fa)[7][4]) {
        constexpr bool TWO = decltype(two)::value;
        PROF(0);
        bar_sync(B_T, 352);
        PROF(1);
        float sc[3][4];
#pragma unroll
        for (int i = 0; i < 3; i++) { sc[i][0] = 0; sc[i][1] = 0; sc[i][2] = 0; sc[i][3] = 0; }
        uint32_t tq[7][4];
#pragma unroll
        for (int i = 0; i < 7; i++) ldsm4t(tq[i][0], tq[i][1], tq[i][2], tq[i][3], lane16 + C_T + i * 512);
#pragma unroll
        for (int i = 0; i < 7; i++) mma16v(sc[i % 3], fa[i], add_bf16x2(tq[i][0], tq[i][2]), add_bf16x2(tq[i][1], tq[i][3]));
        bar_arrive(B_S, 288);
        const uint32_t v0 = pack_bf16((sc[1][0] + sc[2][0]) + sc[0][0], (sc[1][1] + sc[2][1]) + sc[0][1]);
        const uint32_t v1 = pack_bf16((sc[1][2] + sc[2][2]) + sc[0][2], (sc[1][3] + sc[2][3]) + sc[0][3]);
        st_async32(speer0 + so, v0, speer0 + C_SB);
        if (TWO) st_async32(speer0 + so + 128, v1, speer0 + C_SB);
        st_async32(speer1 + so, v0, speer1 + C_SB);
        if (TWO) st_async32(speer1 + so + 128, v1, speer1 + C_SB);
        st_async32(speer2 + so, v0, speer2 + C_SB);
        if (TWO) st_async32(speer2 + so + 128, v1, speer2 + C_SB);
        sts32(sb + so, v0);
        if (TWO) sts32(sb + so + 128, v1);
        __syncwarp();
        if (l == 0) mbar_arrive(sb + C_SB);
      };
      if (lw < 2) {
        uint32_t fa[7][4];
#pragma unroll
        for (int i = 0; i < 7; i++) ldsm4(fa[i][0], fa[i][1], fa[i][2], fa[i][3], fbase + xo + i * 1024);
        scores(std::true_type(), fa);
      } else if (lw == 2) {
        uint32_t fa[7][4];
        mbar_wait(sb + C_AG + par * 32 + (gj >> 1) * 8, ph);
#pragma unroll
        for (int i = 0; i < 7; i++) ldsm4t(fa[i][0], fa[i][1], fa[i][2], fa[i][3], fbase + par * 7168 + i * 256);
        scores(std::false_type(), fa);
      }
      uint32_t uf[4][4];
#pragma unroll
      for (int t = 0; t < 4; t++) ldsm4(uf[t][0], uf[t][1], uf[t][2], uf[t][3], ubase + xo + (t >> 1) * 256 + (t & 1) * 3584);
      char* gp = reinterpret_cast<char*>(g_xch) + par * GSLOT + gwo;
      PROF(2);
      mbar_wait(sb + C_SB, par);
      PROF(3);
      uint32_t r[5][4];
#pragma unroll
      for (int i = 0; i < 5; i++) ldsm4t(r[i][0], r[i][1], r[i][2], r[i][3], lane16 + C_S + i * 512);
      float x0[4] = {0, 0, 0, 0}, x1[4] = {0, 0, 0, 0}, x2[4] = {0, 0, 0, 0};
      mma16v(x0, r[0], idm, idm);
      mma16v(x1, r[2], idm, idm);
      mma16v(x0, r[1], idm, idm);
      mma16v(x1, r[3], idm, idm);
      mma16v(x2, r[4], idm, idm);
      const float y0 = x2[0] + x2[2], y1 = x2[1] + x2[3];
      float m = fmaxf(fmaxf(fmaxf(x0[0], x0[1]), fmaxf(x0[2], x0[3])), fmaxf(fmaxf(fmaxf(x1[0], x1[1]), fmaxf(x1[2], x1[3])), fmaxf(y0, y1)));
      m = fmaxf(m, __shfl_xor_sync(0xffffffffu, m, 1));
      m = fmaxf(m, __shfl_xor_sync(0xffffffffu, m, 2));
      PROF(4);
      const float L = 1.4426950408889634f, mL = -m * L;
      auto ex2p = [&](float x, float y) { return pack_bf16(ex2f(fmaf(x, L, mL)), ex2f(fmaf(y, L, mL))); };
      const uint32_t p0 = ex2p(x0[0], x0[1]);
      const uint32_t p1 = ex2p(x0[2], x0[3]);
      float sa[4] = {0, 0, 0, 0}, oa[4] = {0, 0, 0, 0}, ob[4] = {0, 0, 0, 0};
      const uint32_t ones[4] = {BF_ONE2, BF_ONE2, BF_ONE2, BF_ONE2};
      mma16v(sa, ones, p0, p1);
      mma16v(oa, uf[0], p0, p1);
      mma16v(ob, uf[2], p0, p1);
      const uint32_t p2 = ex2p(x1[0], x1[1]);
      const uint32_t p3 = ex2p(x1[2], x1[3]);
      const uint32_t p4 = ex2p(y0, y1);
      mma16v(sa, ones, p2, p3);
      mma16v(oa, uf[1], p2, p3);
      mma16v(ob, uf[3], p2, p3);
      mma8(sa, BF_ONE2, BF_ONE2, p4);
      bar_sync(B_V, 384);
      uint32_t va[4], vb[4];
      ldsm4(va[0], va[1], va[2], va[3], lane16 + C_V + t0 * 512);
      ldsm4(vb[0], vb[1], vb[2], vb[3], lane16 + C_V + t0 * 512 + 512);
      mma16v(oa, va, p4, p4);
      mma16v(ob, vb, p4, p4);
      const float i0 = rcpf(sa[0]), i1 = rcpf(sa[1]);
      stg_relaxed(gp, tagged(oa[0] * i0, oa[1] * i1, tag));
      stg_relaxed(gp + 2048, tagged(oa[2] * i0, oa[3] * i1, tag));
      stg_relaxed(gp + 4096, tagged(ob[0] * i0, ob[1] * i1, tag));
      stg_relaxed(gp + 6144, tagged(ob[2] * i0, ob[3] * i1, tag));
      const uint32_t tw = clk32();
      bar_arrive(B_PV, 384);
      PROF(5);
      const char* p = reinterpret_cast<const char*>(g_xch) + par * GSLOT + gro;
      ph ^= par;
      par ^= 1;
      if (lw == 3) {
        if (l < 2) mbar_expect(sb + C_AG + par * 32 + l * 8, 3584);
        if (l == 4 && s + 2 < NSEG) mbar_expect(sb + C_SB, 1920);
      }
      uint32_t da[4], db[4];
#pragma unroll
      for (int i = 0; i < 4; i++) {
        const uint32_t pb = mapa(sb, ((a + i) & 3) << 2) + cpeer;
        da[i] = pb + ago + C_MEM + par * 7168 + i * 1792;
        db[i] = pb + C_AG + par * 32 + (i >> 1) * 8;
      }
      uint32_t q0, q1, q2, q3;
      auto fetch = [&](uint4 (&v)[4]) {
#pragma unroll
        for (int i = 0; i < 4; i++) v[i] = ldg_relaxed16(p + i * 256);
      };
      auto reduce = [&](const uint4 (&v)[4]) {
        const uint32_t mk = ~1u;
        float m0[4] = {0, 0, 0, 0}, m1[4] = {0, 0, 0, 0};
        const uint32_t a0[4] = {v[0].x & mk, v[0].y & mk, v[1].x & mk, v[1].y & mk}, a1[4] = {v[0].z & mk, v[0].w & mk, v[1].z & mk, v[1].w & mk};
        const uint32_t a2[4] = {v[2].x & mk, v[2].y & mk, v[3].x & mk, v[3].y & mk}, a3[4] = {v[2].z & mk, v[2].w & mk, v[3].z & mk, v[3].w & mk};
        mma16v(m0, a0, sel, sel);
        mma16v(m1, a1, sel, sel);
        mma16v(m0, a2, sel, sel);
        mma16v(m1, a3, sel, sel);
        const uint32_t k0 = lop3<0x80>(lop3<0x81>(v[0].x, v[0].y, tag), lop3<0x81>(v[0].z, v[0].w, tag), lop3<0x81>(v[1].x, v[1].y, tag));
        const uint32_t k1 = lop3<0x80>(lop3<0x81>(v[1].z, v[1].w, tag), lop3<0x81>(v[2].x, v[2].y, tag), lop3<0x81>(v[2].z, v[2].w, tag));
        const uint32_t k2 = lop3<0x80>(lop3<0x81>(v[3].x, v[3].y, tag), lop3<0x81>(v[3].z, v[3].w, tag), 1u);
        q0 = pack_bf16(m0[0], m0[1]); q1 = pack_bf16(m0[2], m0[3]); q2 = pack_bf16(m1[0], m1[1]); q3 = pack_bf16(m1[2], m1[3]);
        return __all_sync(0xffffffffu, lop3<0x80>(k0, k1, k2) != 0);
      };
      auto gather = [&](bool act) {
        while (clk32() - tw < POLL_DELAY) { }
#pragma unroll 1
        for (uint32_t it = 0; it < POLL_LIMIT; it++) {
          uint4 ga[4];
          fetch(ga);
          if (reduce(ga)) break;
        }
        PROF(6);
        if (act) {
#pragma unroll
          for (int i = 0; i < 4; i++) st_async128(da[i], q0, q1, q2, q3, db[i]);
        }
      };
      if (lw < 3) gather(true); else gather(pact);
      if (s == NSEG - 2 && cl == 0) {
        if (pact && c == 0)
          *reinterpret_cast<uint4*>(g_mem + (size_t)(((15 * 2 + (a >> 1)) * 4 + 3) * 224 + (a & 1) * 112 + j * 28 + prl) * 4) = make_uint4(q0, q1, q2, q3);
        __syncwarp();
        if (l == 0) { fence_gpu(); flag_add(F_M + 15); }
      }
      PROF(7);
    }
    bar_sync(B_V, 384);
    bar_arrive(B_PV, 384);
    char* gw = reinterpret_cast<char*>(g_xch) + GSLOT + gwo;
    stg_relaxed(gw, 0); stg_relaxed(gw + 2048, 0); stg_relaxed(gw + 4096, 0); stg_relaxed(gw + 6144, 0);
  } else {
    asm volatile("setmaxnreg.inc.sync.aligned.u32 216;");
    uint32_t wa[28][4], wb[NOWN][4];
#pragma unroll
    for (int i = 0; i < 28; i++) { wa[i][0] = 0; wa[i][1] = 0; wa[i][2] = 0; wa[i][3] = 0; wb[i % NOWN][0] = 0; wb[i % NOWN][1] = 0; wb[i % NOWN][2] = 0; wb[i % NOWN][3] = 0; }
    const int hf = w >> 2, P = w & 3, town = w == 7 ? 3 : w, tpar = w ^ 4;
    {
      PT(1);
      const uint32_t qa = sb + P_ST + (l >> 4) * 1792 + (l & 15) * 16;
      uint32_t st = 0, sp = 0;
      auto extract = [&](auto isb_t, auto odd) {
        constexpr bool isb = decltype(isb_t)::value;
        {
#pragma unroll
          for (int i = 0; i < 7; i++) {
            constexpr int k0 = decltype(odd)::value * 7;
            const int k = k0 + i;
            uint32_t q[4];
            if (!isb) {
              ldsm4(wa[k][0], wa[k][1], wa[k][2], wa[k][3], qa + i * 3584 + town * 256);
              if (P != 3) ldsm4(wa[14 + k][0], wa[14 + k][1], wa[14 + k][2], wa[14 + k][3], qa + i * 3584 + tpar * 256);
            } else {
              if (k < NPARK) {
                ldsm4(q[0], q[1], q[2], q[3], qa + i * 3584 + town * 256);
                sts128u(sb + P_PARK + hf * (C_V - P_PARK) + (P * NPARK + k) * 512 + l * 16, q);
              } else if (k < NOWN) ldsm4(wb[k % NOWN][0], wb[k % NOWN][1], wb[k % NOWN][2], wb[k % NOWN][3], qa + i * 3584 + town * 256);
              else {
                ldsm4(q[0], q[1], q[2], q[3], qa + i * 3584 + town * 256);
                sts128u(sb + C_B2 + (w * (14 - NOWN) + k - NOWN) * 512 + l * 16, q);
              }
              if (k < 14 - NSH) {
                if (P != 3) {
                  ldsm4(q[0], q[1], q[2], q[3], qa + i * 3584 + tpar * 256);
                  sts128u(sb + C_B + ((hf * 3 + P) * (14 - NSH) + k) * 512 + l * 16, q);
                }
              } else if (P == 3) {
#pragma unroll
                for (int t = 0; t < 3; t++) {
                  uint32_t (&d)[4] = wa[14 + t * NSH + (k - 14 + NSH) % NSH];
                  ldsm4(d[0], d[1], d[2], d[3], qa + i * 3584 + ((1 - hf) * 4 + t) * 256);
                }
              }
            }
          }
        }
      };
      auto phase = [&](auto isb_t) {
        constexpr bool isb = decltype(isb_t)::value;
        uint32_t fo[16][4];
        if constexpr (isb) {
#pragma unroll
          for (int i = 0; i < 16; i++) {
            if ((i & 3) == 0) mbar_wait(sb + C_AF + (i >> 2) * 8, 0);
            ldsm4t(fo[i][0], fo[i][1], fo[i][2], fo[i][3],
                   sb + P_A + (i >> 2) * 16384 + hf * 8192 + ((i & 3) * 16 + (l >> 4) * 8 + (l & 7)) * 128 + (((P * 2 + ((l >> 3) & 1)) ^ (l & 7)) << 4));
          }
          __syncwarp();
          if (l == 0) mbar_arrive(sb + C_AE);
          PT(27);
        }
#pragma unroll 1
        for (int g = 0; g < 4; g++) {
          float acc[56];
#pragma unroll
          for (int i = 0; i < 56; i++) acc[i] = 0.f;
          uint32_t prev = 0;
#pragma unroll (isb ? 4 : 1)
          for (int e = 0; e < 4; e++) {
            if (!isb && g == 0) mbar_wait(sb + C_AF + e * 8, 1);
            mbar_wait(sb + C_PF + st * 8, sp);
            if (isb && g == 0 && e == 0) PT(28);
            const uint64_t db = make_desc(sb + P_R + st * 14336, 16, 1024, 1);
            const uint64_t da = make_desc(sb + P_A + e * 16384 + hf * 8192, 16, 1024, 1);
            wg_fence();
#pragma unroll
            for (int kk = 0; kk < 4; kk++) {
              if constexpr (isb) wg_rs112(acc, fo[e * 4 + kk][0], fo[e * 4 + kk][1], fo[e * 4 + kk][2], fo[e * 4 + kk][3], db + kk * 2, 1);
              else wg_ss112<0>(acc, da + kk * 2, db + kk * 2, 1);
            }
            wg_commit();
            if (e == XE) {
              if (g == 0) { if (!isb && hf == 1) extract(std::true_type(), std::integral_constant<int, 1>()); }
              else if (((g - 1) >> 1) == hf) {
                if (g & 1) extract(isb_t, std::integral_constant<int, 0>()); else extract(isb_t, std::integral_constant<int, 1>());
              }
            }
            wg_wait<1>();
            if (e > 0 && l < 4 && P == 0) mbar_arrive_remote(mapa(sb + C_PE + prev * 8, a * 4 + l));
            prev = st;
            if (++st == P_NS) { st = 0; sp ^= 1; }
          }
          wg_wait<0>();
          PT(2 + 3 * (g + (isb ? 0 : 4)));
          if (l < 4 && P == 0) mbar_arrive_remote(mapa(sb + C_PE + prev * 8, a * 4 + l));
          if (!isb && g == 3 && l == 0) mbar_arrive(sb + C_AE + 8);
          if (!isb || g > 0) bar_sync(B_SR, 288);
          const float sc = isb ? 1.f : 0.0625f;
          if (w < 7) {
#pragma unroll
            for (int i = 0; i < 7; i++)
              stsm4(qa + i * 3584 + w * 256, pack_bf16(acc[8 * i] * sc, acc[8 * i + 1] * sc), pack_bf16(acc[8 * i + 2] * sc, acc[8 * i + 3] * sc),
                    pack_bf16(acc[8 * i + 4] * sc, acc[8 * i + 5] * sc), pack_bf16(acc[8 * i + 6] * sc, acc[8 * i + 7] * sc));
          }
          fence_async_smem();
          bar_sync(B_ST, 288);
          PT(3 + 3 * (g + (isb ? 0 : 4)));
          PT(4 + 3 * (g + (isb ? 0 : 4)));
        }
      };
      phase(std::true_type());
      phase(std::false_type());
      if (hf == 1) extract(std::false_type(), std::integral_constant<int, 1>());
#pragma unroll
      for (int k = 0; k < NPARK; k++) lds128u(wb[k], sb + P_PARK + hf * (C_V - P_PARK) + (P * NPARK + k) * 512 + l * 16);
      bar_sync(B_SR, 288);
      bar_sync(B_INIT, 288);
#pragma unroll
      for (int k = 0; k < 2 * NRE; k++) sts128u(sb + C_A1 + (w * 2 * NRE + k) * 512 + l * 16, wa[k < NRE ? k : 14 + k - NRE]);
      PT(26);
    }
    const uint32_t st4 = opaque(sb + hf * 256 + l * 4);
    const uint32_t l16 = opaque(sb + l * 16);
    const uint32_t sm4 = opaque(sb + (l < 16 ? tpar : town) * 512 + hf * 256 + (l & 15) * 16);
    uint32_t mo = C_MEM + hf * 3584;
    int xi = 2;
    uint32_t ag = sb + C_AG + hf * 8, ph = 0;
    for (int s = 0; s < NSEG; s++) {
      uint32_t b[2][14];
      float t0[4] = {0, 0, 0, 0}, t1[4] = {0, 0, 0, 0};
      PROFM(8);
#pragma unroll
      for (int k = 0; k < 2 * NRE; k++) {
        lds128u(wa[k < NRE ? k : 14 + k - NRE], l16 + C_A1 + (w * 2 * NRE + k) * 512);
      }
      PROFM(0);
      if (P != 3) {
        float t2[4] = {0, 0, 0, 0}, t3[4] = {0, 0, 0, 0};
        mbar_wait(ag, ph);
        ld_quarter(b[0], l16 + mo);
        ld_quarter(b[1], l16 + mo + 1792);
#pragma unroll
        for (int i = 0; i < 7; i++) {
          mma16v((i & 1) ? t1 : t0, wa[i], b[0][2 * i], b[0][2 * i + 1]);
          mma16v((i & 1) ? t3 : t2, wa[14 + i], b[0][2 * i], b[0][2 * i + 1]);
        }
        uint32_t aq[NPAR][4], q4[14 - NOWN][4];
        const uint32_t bq = l16 + C_B + (hf * 3 + P) * (14 - NSH) * 512;
#pragma unroll
        for (int i = 7; i < 14; i++) {
          mma16v((i & 1) ? t1 : t0, wa[i], b[1][2 * (i - 7)], b[1][2 * (i - 7) + 1]);
          mma16v((i & 1) ? t3 : t2, wa[14 + i], b[1][2 * (i - 7)], b[1][2 * (i - 7) + 1]);
        }
        stsm4(sm4 + C_T, pack_bf16(t2[0] + t3[0], t2[1] + t3[1]), pack_bf16(t2[2] + t3[2], t2[3] + t3[3]),
              pack_bf16(t0[0] + t1[0], t0[1] + t1[1]), pack_bf16(t0[2] + t1[2], t0[3] + t1[3]));
        if (s < NSEG - 1) bar_arrive(B_T, 352);
        PROFM(4);
        if (s < NSEG - 1) bar_sync(B_S, 288);
        PROFM(6);
        {
          const float z = __uint_as_float(lds32(sb + C_ZERO));
#pragma unroll
          for (int i = 0; i < 4; i++) { t0[i] = z; t1[i] = z; t2[i] = z; t3[i] = z; }
        }
#pragma unroll
        for (int i = 0; i < NPAR; i++) lds128u(aq[i], bq + i * 512);
#pragma unroll
        for (int i = 0; i < 14 - NOWN; i++) lds128u(q4[i], l16 + C_B2 + (w * (14 - NOWN) + i) * 512);
#pragma unroll
        for (int i = 0; i < 14; i++) {
          mma16v((i & 1) ? t1 : t0, i < NOWN ? wb[i % NOWN] : q4[i < NOWN ? 0 : i - NOWN], b[i / 7][2 * (i % 7)], b[i / 7][2 * (i % 7) + 1]);
          if (i < NPAR) mma16v((i & 1) ? t3 : t2, aq[i % NPAR], b[i / 7][2 * (i % 7)], b[i / 7][2 * (i % 7) + 1]);
        }
        {
          float ws[4];
          bar_sync(B_W, 256);
          lds128(ws, l16 + C_W + (hf * 3 + P) * 512);
          stsm4(sm4 + C_V, pack_bf16((t2[0] + t3[0]) + ws[0], (t2[1] + t3[1]) + ws[1]), pack_bf16((t2[2] + t3[2]) + ws[2], (t2[3] + t3[3]) + ws[3]),
                pack_bf16(t0[0] + t1[0], t0[1] + t1[1]), pack_bf16(t0[2] + t1[2], t0[3] + t1[3]));
        }
        bar_arrive(B_V, 384);
        bar_arrive(B_VP, 256);
        PROFM(5);
        bar_sync(B_PV, 384);
      } else {
        mbar_wait(ag, ph);
        ld_quarter(b[0], l16 + mo);
        ld_quarter(b[1], l16 + mo + 1792);
        const bool pubm = w == 3 && cl == 0 && j == 0 && s < NSEG - 1;
        if (pubm) {
          fence_async_smem();
          if (elect_one()) { bulk_store(g_mem + (size_t)((((s >> 2) * 2 + (a >> 1)) * 4 + (s & 3)) * 224 + (a & 1) * 112) * 4, sb + mo, 1792); bulk_commit(); }
          __syncwarp();
        }
#pragma unroll
        for (int i = 0; i < 14; i++) mma16v((i & 1) ? t1 : t0, wa[i], b[i / 7][2 * (i % 7)], b[i / 7][2 * (i % 7) + 1]);
        sts32(st4 + C_T + 3 * 512, pack_bf16(t0[0] + t1[0], t0[1] + t1[1]));
        sts32(st4 + C_T + 3 * 512 + 128, pack_bf16(t0[2] + t1[2], t0[3] + t1[3]));
        if (s < NSEG - 1) bar_arrive(B_T, 352);
        PROFM(4);
        float sh[3][4];
        const float z = __uint_as_float(lds32(sb + C_ZERO));
#pragma unroll
        for (int t = 0; t < 3; t++) { sh[t][0] = z; sh[t][1] = z; sh[t][2] = z; sh[t][3] = z; }
#pragma unroll
        for (int i = 0; i < NSH; i++)
#pragma unroll
          for (int t = 0; t < 3; t++) mma16v(sh[t], wa[14 + t * NSH + i], b[1][2 * (7 - NSH + i)], b[1][2 * (7 - NSH + i) + 1]);
#pragma unroll
        for (int i = NPAR; i < 14 - NSH; i++)
#pragma unroll
          for (int t = 0; t < 3; t++) {
            uint32_t q[4];
            lds128u(q, l16 + C_B + ((hf * 3 + t) * (14 - NSH) + i) * 512);
            mma16v(sh[t], q, b[i / 7][2 * (i % 7)], b[i / 7][2 * (i % 7) + 1]);
          }
#pragma unroll
        for (int t = 0; t < 3; t++) sts128(l16 + C_W + (hf * 3 + t) * 512, sh[t][0], sh[t][1], sh[t][2], sh[t][3]);
        bar_arrive(B_W, 256);
        {
          const float z2 = __uint_as_float(lds32(sb + C_ZERO));
#pragma unroll
          for (int i = 0; i < 4; i++) { t0[i] = z2; t1[i] = z2; }
        }
#pragma unroll
        for (int i = 0; i < NOWN; i++) mma16v((i & 1) ? t1 : t0, wb[i], b[i / 7][2 * (i % 7)], b[i / 7][2 * (i % 7) + 1]);
#pragma unroll
        for (int i = NOWN; i < 14; i++) {
          uint32_t q4[4];
          asm volatile("ld.shared.v4.u32 {%0,%1,%2,%3}, [%4];" : "=r"(q4[0]), "=r"(q4[1]), "=r"(q4[2]), "=r"(q4[3])
                       : "r"(l16 + C_B2 + (w * (14 - NOWN) + i - NOWN) * 512) : "memory");
          mma16v((i & 1) ? t1 : t0, q4, b[i / 7][2 * (i % 7)], b[i / 7][2 * (i % 7) + 1]);
        }
        sts32(st4 + C_V + 3 * 512, pack_bf16(t0[0] + t1[0], t0[1] + t1[1]));
        sts32(st4 + C_V + 3 * 512 + 128, pack_bf16(t0[2] + t1[2], t0[3] + t1[3]));
        bar_arrive(B_V, 384);
        PROFM(5);
        if (w == 3) {
          bar_arrive(B_VP, 256);
          if (pubm) {
            bulk_wait_all();
            __syncwarp();
            if (l == 0) flag_add(F_M + (s >> 2));
          }
          bar_sync(B_PV, 384);
        }
        else {
          bar_sync(B_VP, 256);
          bar_sync(B_PV, 384);
          const uint32_t vp = st4 - 256 + C_VP + (s & 1) * 1792;
#pragma unroll
          for (int t = 0; t < 7; t++) {
            uint32_t v0, v1, v2, v3;
            ldsm4(v0, v1, v2, v3, l16 + C_V + t * 512);
            sts32(vp + t * 256, add_bf16x2(v0, v2));
            sts32(vp + t * 256 + 128, add_bf16x2(v1, v3));
          }
          fence_async_smem();
          __syncwarp();
          if (elect_one()) {
            bulk_store(g_Vt + (size_t)((s * 80 + 64 + h) * 56 + j * 14) * 32, sb + C_VP + (s & 1) * 1792, 1792);
            bulk_commit();
          }
          __syncwarp();
          if (s + 2 < NSEG) {
            load_seg(sb, xi, s + 2, h, j);
            xi = xi == 2 ? 0 : xi + 1;
          }
          bulk_wait_all();
          __syncwarp();
          if (l == 0) flag_add(F_C + s);
          __syncwarp();
          PROFM(9);
        }
      }
      mo = 2 * (C_MEM + hf * 3584) + 7168 - mo;
      ag = 2 * (sb + C_AG + hf * 8) + 32 - ag;
      ph ^= s & 1;
    }
  }
  __syncthreads();
  cluster_sync_all();
}
enum { T_FFN1 = 0, T_U = 1, T_P = 2, T_FFN2 = 3, T_FIN = 4, T_FINN = 5, T_END = 7 };
constexpr int MAX_PAIRS = 40, MAX_CHUNKS = 32;
struct Schedule { uint16_t c[MAX_PAIRS][MAX_CHUNKS]; };
struct BulkMaps { CUtensorMap wg, wu, wd, x, out, vt; };
constexpr int NST = 7, STG = 16384;
constexpr int K_XF = 0, K_XE = 56, K_RF = 112, K_RE = 168, K_GO = 224;
constexpr int K_X = 1024, K_R = K_X + 7 * 16384, K_SMEM = K_R + NST * STG + 1024;
constexpr int K_FP = K_X, K_FG = K_X + 49152, K_FX = K_X + 81920;
constexpr int K_NV = K_X + 40960, K_NG = K_X + 90112, K_NX = K_X + 98304;
enum { KB_SIG = 1, KB_WG = 2 };
#define FIN_PACE 450
#define TRANSP 1
#define DEFER_U 1
#define DEFER_F 1
#define BTIME(i)
#define BTIMEW(i, who)
#define BT0()
#define BT1(i)

struct Ring {
  uint32_t st = 0, ph = 0;
  __device__ __forceinline__ void next() { if (++st == NST) { st = 0; ph ^= 1; } }
};

__device__ __forceinline__ void layer_norm_segment(uint32_t sb, const __nv_bfloat16* __restrict__ x, int seg) {
  const int w = threadIdx.x >> 5, l = threadIdx.x & 31;
  uint32_t vv[3][7];
#pragma unroll
  for (int q = 0; q < 3; q++) {
    const uint32_t* row = reinterpret_cast<const uint32_t*>(x + (size_t)(seg * SEG + min(w + 12 * q, SEG - 1)) * DM);
#pragma unroll
    for (int i = 0; i < 7; i++) vv[q][i] = __ldg(row + l + 32 * i);
  }
#pragma unroll
  for (int q = 0; q < 3; q++) {
    const int r = w + 12 * q;
    if (r >= SEG) break;
    const uint32_t (&v)[7] = vv[q];
    float sum = 0.f;
#pragma unroll
    for (int i = 0; i < 7; i++) sum += bf_lo(v[i]) + bf_hi(v[i]);
#pragma unroll
    for (int o = 16; o; o >>= 1) sum += __shfl_xor_sync(0xffffffffu, sum, o);
    const float mean = sum * (1.f / DM);
    float sq = 0.f;
#pragma unroll
    for (int i = 0; i < 7; i++) { const float a = bf_lo(v[i]) - mean, b = bf_hi(v[i]) - mean; sq += a * a + b * b; }
#pragma unroll
    for (int o = 16; o; o >>= 1) sq += __shfl_xor_sync(0xffffffffu, sq, o);
    const float mb = bf_round(mean), sd = bf_round(sqrtf(bf_round(bf_round(sq * (1.f / DM)) + 1e-5f)));
#pragma unroll
    for (int i = 0; i < 7; i++)
      sts32(sb + K_R + ((l >> 2) + 8 * i) * 512 + (r >> 3) * 128 + (r & 7) * 16 + (l & 3) * 4,
            pack_bf16(__fdividef(bf_round(bf_lo(v[i]) - mb), sd), __fdividef(bf_round(bf_hi(v[i]) - mb), sd)));
  }
  fence_async_smem();
  __syncthreads();
  BTIME(38);
  if (threadIdx.x < 57) {
    const int t = threadIdx.x;
    if (t < 56) bulk_store(g_xc + (size_t)(((seg >> 2) * 56 + t) * 16 + (seg & 3) * 4) * 32, sb + K_R + t * 512, 512);
    else bulk_store(g_xq + (size_t)seg * 56 * 128, sb + K_R, 28672);
    bulk_commit();
    bulk_wait_all();
  }
  __syncthreads();
  if (threadIdx.x == 0) { fence_gpu(); flag_add(F_LN + (seg >> 2)); }
}

__global__ void __cluster_dims__(2, 1, 1) __launch_bounds__(384, 1)
bulk_kernel(const __grid_constant__ BulkMaps maps, const __grid_constant__ Schedule sched, const __nv_bfloat16* __restrict__ x) {
  extern __shared__ uint8_t smem_raw[];
  const uint32_t sb = (smem_u32(smem_raw) + 1023) & ~1023u;
  const int tid = threadIdx.x, w = __shfl_sync(0xffffffffu, tid >> 5, 0), l = tid & 31;
  const int rk = blockIdx.x & 1, pair = blockIdx.x >> 1;
  BTIME(0);
  if (tid == 0) {
    for (int i = 0; i < 7; i++) { mbar_init(sb + K_XF + i * 8, 1); mbar_init(sb + K_XE + i * 8, 2); }
    for (int i = 0; i < NST; i++) { mbar_init(sb + K_RF + i * 8, 1); mbar_init(sb + K_RE + i * 8, 4); }
    sts32(sb + K_GO, 0);
    asm volatile("fence.mbarrier_init.release.cluster;" ::: "memory");
  }
  if (tid == 32) {
    asm volatile("prefetch.tensormap [%0];" ::"l"(&maps.wg) : "memory");
    asm volatile("prefetch.tensormap [%0];" ::"l"(&maps.wu) : "memory");
    asm volatile("prefetch.tensormap [%0];" ::"l"(&maps.wd) : "memory");
  }
  for (int seg = blockIdx.x; seg < NSEG; seg += gridDim.x) layer_norm_segment(sb, x, seg);
  __syncthreads();
  asm volatile("barrier.cluster.arrive.relaxed.aligned;\n barrier.cluster.wait.aligned;" ::: "memory");

  if (w >= 8) {
    asm volatile("setmaxnreg.dec.sync.aligned.u32 40;");
    if (w == 8) {
      uint32_t xph = 1, ndep = 0;
      auto dep = [&]() {
        ndep++;
#pragma unroll 1
        for (uint32_t it = 0; it < DEP_LIMIT; it++) {
          uint32_t v;
          asm volatile("ld.acquire.cta.shared.u32 %0, [%1];" : "=r"(v) : "r"(sb + K_GO) : "memory");
          if (v >= ndep) break;
          __nanosleep(20);
        }
      };
      const uint32_t su = __shfl_sync(0xffffffffu, sb, 0);
      uint32_t rbar = su + K_RF, rdst = su + K_R, rph = 1;
      uint32_t tnext = clk32();
      auto pace = [&](uint32_t cycles) {
        while ((int32_t)(clk32() - tnext) < 0) { }
        tnext = clk32() + cycles;
      };
      auto stage = [&](auto issue, uint32_t cycles = 0) {
        { BT0(); mbar_wait(rbar + (K_RE - K_RF), rph); BT1(0); }
        if (cycles) pace(cycles);
        if (elect_one()) issue(rbar, rdst);
        rbar += 8; rdst += STG;
        if (rbar == su + K_RF + NST * 8) { rbar = su + K_RF; rdst = su + K_R; rph ^= 1; }
      };
      auto xload = [&](int k, const uint32_t* src) {
        mbar_wait(su + K_XE + k * 8, xph);
        if (elect_one()) { mbar_expect(su + K_XF + k * 8, 16384); bulk_load(su + K_X + k * 16384, src, 16384, su + K_XF + k * 8); }
      };
      for (int ci = 0; ci < MAX_CHUNKS; ci++) {
        const int cd = __shfl_sync(0xffffffffu, (int)sched.c[pair][ci], 0), type = cd >> 13, T = (cd >> 10) & 7, i0 = (cd >> 4) & 63, cnt = cd & 15;
        if (type == T_END) break;
        const int tile = T * 2 + rk;
        if (type >= T_FIN) {
          const bool wide = type == T_FIN;
          const int seg = T * 8 + (wide ? i0 * 2 + rk : i0 >> 1);
          auto load_p = [&]() {
            dep();
            if (elect_one()) {
              mbar_expect(su + K_XF, 12288);
              bulk_load(su + K_FP, g_P + (size_t)seg * 80 * 128, 12288, su + K_XF);
              mbar_expect(su + K_XF + 16, 28672);
              bulk_load(su + K_FP + 12288, g_P + (size_t)seg * 80 * 128 + 3072, 28672, su + K_XF + 16);
            }
          };
          dep();
          if (wide) {
            const uint32_t* src = g_Vt + (size_t)seg * 80 * 56 * 32;
#pragma unroll 1
            for (int st = 0; st < 40; st++) {
              if (st == NST) {
                for (int k = 0; k < 3; k++) mbar_wait(su + K_XE + k * 8, xph);
                load_p();
              }
              if (st == 16) {
                for (int k = 3; k < 7; k++) mbar_wait(su + K_XE + k * 8, xph);
                dep();
                if (elect_one()) {
                  mbar_expect(su + K_XF + 8, 2 * 28672);
                  bulk_load(su + K_FG, g_G + (size_t)seg * 4 * 56 * 32, 28672, su + K_XF + 8);
#pragma unroll 1
                  for (int b = 0; b < 7; b++) tma2d(su + K_FX + b * 4096, &maps.x, b * 64, seg * SEG, su + K_XF + 8);
                  for (int k = 3; k < 7; k++) mbar_arrive(su + K_XF + k * 8);
                }
              }
              if (st == 32) dep();
              stage([&](uint32_t bar, uint32_t dst) { mbar_expect(bar, 14336); bulk_load_last(dst, src, 14336, bar); }, FIN_PACE);
              src += 2 * 56 * 32;
            }
          } else {
            const int mt0 = (i0 & 1) * 4 + rk * 2, nb = mt0 == 6 ? 1 : 2;
#pragma unroll 1
            for (int st = 0; st < NST; st++)
              stage([&](uint32_t bar, uint32_t dst) { mbar_expect(bar, 16384); tma2d(dst, &maps.vt, mt0 * 128, seg * 80 + st * 8, bar); }, FIN_PACE);
            for (int k = 0; k < 7; k++) mbar_wait(su + K_XE + k * 8, xph);
            dep();
            if (elect_one()) {
              mbar_expect(su + K_XF + 8, nb * 8192);
#pragma unroll 1
              for (int b = 0; b < 4; b++) bulk_load(su + K_NG + b * 2048, g_G + ((size_t)(seg * 4 + b) * 56 + mt0 * 8) * 32, nb * 1024, su + K_XF + 8);
#pragma unroll 1
              for (int b = 0; b < nb; b++) tma2d(su + K_NX + b * 4096, &maps.x, (mt0 + b) * 64, seg * SEG, su + K_XF + 8);
              for (int k = 4; k < 7; k++) mbar_arrive(su + K_XF + k * 8);
            }
            dep();
            if (elect_one()) {
              mbar_expect(su + K_XF + 24, 49152);
#pragma unroll 1
              for (int st = NST; st < 10; st++) tma2d(su + K_NV + (st - NST) * 16384, &maps.vt, mt0 * 128, seg * 80 + st * 8, su + K_XF + 24);
            }
            load_p();
          }
          xph ^= 1;
        } else if (type == T_FFN2) {
          const int c0 = i0 * 256 + rk * 128;
          const bool two = !(i0 && rk);
          const uint32_t bytes = i0 ? 12288 : 16384;
          const uint32_t* src = g_H + (size_t)tile * 224 * 512;
          dep();
          int k = 0;
#pragma unroll 1
          for (int kb = 0; kb < 28; kb++) {
            xload(k, src);
            src += 4096;
            if (++k == 7) { k = 0; xph ^= 1; }
#pragma unroll
            for (int hb = 0; hb < 2; hb++)
              stage([&](uint32_t bar, uint32_t dst) {
                mbar_expect(bar, bytes);
                tma2d_mc(dst + rk * 8192, &maps.wd, c0, kb * 64 + hb * 32, bar, 3);
                if (two) tma2d_mc(dst + rk * 8192 + 4096, &maps.wd, c0 + 64, kb * 64 + hb * 32, bar, 3);
              });
          }
        } else {
          const uint32_t* xs = g_xc + (size_t)tile * 56 * 512;
          dep();
          if (type == T_FFN1) {
            const CUtensorMap* tm = rk ? &maps.wu : &maps.wg;
#pragma unroll 1
            for (int n = 0; n < cnt * 7; n++) {
              const int it = n / 7, kb = n - it * 7, c0 = (i0 + it) * 128;
              if (it == 0) xload(kb, xs + kb * 4096);
#pragma unroll
              for (int hb = 0; hb < 2; hb++)
                stage([&](uint32_t bar, uint32_t dst) {
                  mbar_expect(bar, 16384);
                  tma2d_mc(dst + rk * 8192, tm, c0, kb * 64 + hb * 32, bar, 3);
                  tma2d_mc(dst + rk * 8192 + 4096, tm, c0 + 64, kb * 64 + hb * 32, bar, 3);
                });
            }
          } else {
            const bool isp = type == T_P;
            const uint32_t* src = (isp ? g_A + (size_t)i0 * 2 * 56 * 28 * 32 : g_B + (size_t)i0 * 56 * 28 * 32) + rk * 1792;
            const int npass = isp ? 2 * cnt : cnt;
#pragma unroll 1
            for (int p = 0; p < npass; p++) {
              if (!isp || !(p & 1)) dep();
#pragma unroll 1
              for (int kb = 0; kb < 7; kb++) {
                if (p == 0) xload(kb, xs + kb * 4096);
#pragma unroll
                for (int hb = 0; hb < 2; hb++) {
                  stage([&](uint32_t bar, uint32_t dst) { mbar_expect(bar, 14336); bulk_load_mc(dst + rk * 7168, src, 7168, bar, 3); });
                  src += 3584;
                }
              }
              if (isp && (p & 1)) {
                dep();
#pragma unroll 1
                for (int hb = 0; hb < 2; hb++)
                  stage([&](uint32_t bar, uint32_t dst) { mbar_expect(bar, 14336); bulk_load(dst, g_mem + (size_t)(tile * 2 + hb) * 3584, 14336, bar); });
              }
            }
          }
          xph ^= 1;
        }
      }
    } else if (w == 10) {
      uint32_t n = 0;
      auto dep = [&](int f, int cntf, unsigned target) {
        wait_flags(f, cntf, target);
        n++;
        if (l == 0) asm volatile("st.release.cta.shared.u32 [%0], %1;" ::"r"(sb + K_GO), "r"(n) : "memory");
      };
      for (int ci = 0; ci < MAX_CHUNKS; ci++) {
        const int cd = sched.c[pair][ci], type = cd >> 13, T = (cd >> 10) & 7, i0 = (cd >> 4) & 63, cnt = cd & 15;
        if (type == T_END) break;
        const int tile = T * 2 + rk;
        if (type >= T_FIN) {
          const int seg = T * 8 + (type == T_FIN ? i0 * 2 + rk : i0 >> 1);
          dep(F_U + (seg >> 2) * 16, 16, 2);
          if (type == T_FIN) { dep(F_P + (seg >> 2), 1, 16); dep(F_G + (seg >> 2), 1, 2); dep(F_C + seg, 1, 64); }
          else { dep(F_G + (seg >> 2), 1, 2); dep(F_C + seg, 1, 64); BTIMEW(30, 320); dep(F_P + (seg >> 2), 1, 16); BTIMEW(29, 320); }
        } else if (type == T_FFN2) {
          dep(F_H + tile, 1, 14);
        } else {
          dep(F_LN + tile, 1, 4);
          for (int it = 0; it < cnt; it++) {
            if (type == T_U) { if (ci == 0) BTIMEW(33, 320); dep(F_B + ((i0 + it) >> 1), 1, 4); if (ci == 0) BTIMEW(34, 320); }
            if (type == T_P) { dep(F_A + i0 + it, 1, 4); dep(F_M + tile, 1, tile == 15 ? 76 : 16); if (T == 7) BTIMEW(26, 320); }
          }
        }
      }
      unsigned done = 0;
      if (l == 0) done = atomicAdd(&g_flag[F_DONE], 1);
      if (__shfl_sync(0xffffffffu, done, 0) == gridDim.x - 1)
        for (int i = l; i < F_COUNT; i += 32) g_flag[i] = 0;
    } else if (w == 9) {
      for (int ci = 0; ci < MAX_CHUNKS; ci++) {
        const int cd = sched.c[pair][ci], type = cd >> 13, T = (cd >> 10) & 7, i0 = (cd >> 4) & 63, cnt = cd & 15;
        if (type == T_END) break;
        if (type >= T_FIN) continue;
        const int tile = T * 2 + rk;
        for (int it = 0; it < cnt; it++) {
          bar_sync(KB_SIG, 288);
          if (l == 0) {
            fence_gpu();
            flag_add(type == T_U ? F_U + tile * 16 + ((i0 + it) >> 1) : (type == T_P ? F_P : (type == T_FFN1 ? F_H : F_G)) + tile);
            if (ci == 0) BTIMEW(37, 288);
            if (type == T_P && T == 7) BTIMEW(28, 288);
          }
          __syncwarp();
        }
      }
    }
  } else {
    asm volatile("setmaxnreg.inc.sync.aligned.u32 232;");
    const int wg = w >> 2, wq = w & 3, g4 = l >> 2, c = l & 3;
    const bool lead = (tid & 127) == 0;
    const uint32_t re_peer = mapa(sb + K_RE, rk ^ 1);
    Ring r;
    uint32_t xph = 0;
    auto release = [&](uint32_t st) { if (lead) { mbar_arrive(sb + K_RE + st * 8); mbar_arrive_remote(re_peer + st * 8); } };
    uint32_t prev = 0;
    auto pass = [&](auto mode, auto& acc, bool first, bool xwait, int xrel, auto side) {
      constexpr int MODE = decltype(mode)::value;
#pragma unroll 1
      for (int k = 0; k < 7; k++) {
        if (xwait) { BT0(); mbar_wait(sb + K_XF + k * 8, xph); BT1(1); }
        const uint64_t da = make_desc(sb + K_X + k * 16384 + wg * 1024, 2048, 128, 0);
#pragma unroll
        for (int hb = 0; hb < 2; hb++) {
          { BT0(); mbar_wait(sb + K_RF + r.st * 8, r.ph); BT1(0); }
          const uint64_t db = MODE == 0 ? make_desc(sb + K_R + r.st * STG, 3584, 128, 0) : make_desc(sb + K_R + r.st * STG, 4096, 1024, 1);
          wg_fence();
#pragma unroll
          for (int kk = 0; kk < 2; kk++) {
            if constexpr (MODE == 0) wg_ss224<0>(acc, da + (hb * 2 + kk) * 256, db + kk * 448, 1);
            else if constexpr (MODE == 1) wg_ss256t<0>(acc, da + (hb * 2 + kk) * 256, db + kk * 128, 1);
            else wg_ss192t<0>(acc, da + (hb * 2 + kk) * 256, db + kk * 128, 1);
          }
          wg_commit();
          { BT0(); wg_wait<1>(); BT1(2); }
          if (hb == 1 || k > 0 || !first) release(prev);
          if (hb == 0 && lead) {
            if (k > 0) { if (k - 1 < xrel) mbar_arrive(sb + K_XE + (k - 1) * 8); }
            else if (!first) mbar_arrive(sb + K_XE + 48);
          }
          side(hb);
          prev = r.st;
          r.next();
        }
      }
    };
    auto zero = [](auto& acc) {
#pragma unroll
      for (int i = 0; i < (int)(sizeof(acc) / 4); i++) acc[i] = 0.f;
    };
    auto drain = [&](bool xrel) {
      wg_wait<0>();
      release(prev);
      if (lead && xrel) mbar_arrive(sb + K_XE + 48);
    };
    auto none = [](int) {};
    for (int ci = 0; ci < MAX_CHUNKS; ci++) {
      const int cd = sched.c[pair][ci], type = cd >> 13, T = (cd >> 10) & 7, i0 = (cd >> 4) & 63, cnt = cd & 15;
      BTIME(1 + ci);
      if (type == T_END) break;
      const int tile = T * 2 + rk, sseg = tile * 4 + wg * 2 + (wq >> 1);
      if (type == T_U) {
        uint32_t pend[56];
#pragma unroll
        for (int n = 0; n < 56; n++) pend[n] = 0;
        uint32_t* o = nullptr;
        auto put = [&](int hb) {
#pragma unroll
          for (int q = 0; q < 4; q++) o[(hb * 2 + (q >> 1)) * 32 + (q & 1) * 1792] = transpose8(pend[hb * 4 + q]);
          if (hb) {
#pragma unroll
            for (int n = 0; n < 48; n++) pend[n] = pend[n + 8];
            o += 128;
          }
        };
        for (int it = 0; it < cnt; it++) {
          float acc[112];
          zero(acc);
          pass(std::integral_constant<int, 0>(), acc, true, it == 0, it == cnt - 1 ? 7 : 0, [&](int hb) { if (DEFER_U && it > 0) put(hb); });
          if (DEFER_U && it > 0) bar_arrive(KB_SIG, 288);
          drain(it == cnt - 1);
          if (ci == 0) BTIME(35);
          const int i = i0 + it;
          o = g_Vt + ((size_t)(sseg * 80 + (i >> 1) * 4 + (wq & 1) * 2) * 56 + (i & 1) * 28) * 32 + l;
#pragma unroll
          for (int n = 0; n < 56; n++) pend[n] = pack_bf16(acc[2 * n], acc[2 * n + 1]);
          if (!DEFER_U || it == cnt - 1) {
            BT0();
#pragma unroll 1
            for (int k = 0; k < 7; k++) { put(0); put(1); }
            if (ci == 0) BTIME(36);
            bar_arrive(KB_SIG, 288);
            BT1(3);
          }
        }
        xph ^= 1;
      } else if (type == T_FFN1) {
        uint32_t pend[64];
#pragma unroll
        for (int n = 0; n < 64; n++) pend[n] = 0;
        uint32_t* o = nullptr;
        auto put = [&](int hb) {
#pragma unroll
          for (int q = 0; q < 2; q++) {
            const uint32_t gp = pend[hb * 4 + 2 * q], up = pend[hb * 4 + 2 * q + 1];
            const uint32_t sp = pack_bf16(silu(bf_lo(gp)), silu(bf_hi(gp)));
            o[hb * 512 + q * 32] = pack_bf16(bf_lo(sp) * bf_lo(up), bf_hi(sp) * bf_hi(up));
          }
          if (hb) {
#pragma unroll
            for (int n = 0; n < 56; n++) pend[n] = pend[n + 8];
            o += 1024;
          }
        };
        for (int it = 0; it < cnt; it++) {
          float acc[128];
          zero(acc);
          pass(std::integral_constant<int, 1>(), acc, true, it == 0, it == cnt - 1 ? 7 : 0, [&](int hb) { if (DEFER_F && it > 0) put(hb); });
          if (DEFER_F && it > 0) { put(0); put(1); bar_arrive(KB_SIG, 288); }
          drain(it == cnt - 1);
          o = g_H + ((size_t)(tile * 224 + (i0 + it) * 16) * 16 + wg * 8 + wq * 2) * 32 + l;
#pragma unroll
          for (int n = 0; n < 32; n++) {
            pend[2 * n] = pack_bf16(acc[2 * n], acc[2 * n + 1]);
            pend[2 * n + 1] = pack_bf16(acc[64 + 2 * n], acc[65 + 2 * n]);
          }
          if (!DEFER_F || it == cnt - 1) {
            BT0();
#pragma unroll 1
            for (int k = 0; k < 8; k++) { put(0); put(1); }
            bar_arrive(KB_SIG, 288);
            BT1(3);
          }
        }
        xph ^= 1;
      } else if (type == T_FFN2) {
        uint32_t* o = g_G + ((size_t)(sseg * 4 + (wq & 1) * 2) * 56 + i0 * 32) * 32 + l;
        uint32_t pend[64];
        auto ffn2 = [&](auto mode, auto& acc) {
          zero(acc);
#pragma unroll 1
          for (int q = 0; q < 4; q++) { pass(mode, acc, q == 0, true, 7, none); xph ^= 1; }
          drain(true);
#pragma unroll
          for (int n = 0; n < 64; n++) pend[n] = n < (int)(sizeof(acc) / 8) ? pack_bf16(acc[(2 * n) % (sizeof(acc) / 4)], acc[(2 * n + 1) % (sizeof(acc) / 4)]) : 0;
        };
        if (i0 == 0) { float acc[128]; ffn2(std::integral_constant<int, 1>(), acc); }
        else { float acc[96]; ffn2(std::integral_constant<int, 2>(), acc); }
#pragma unroll 1
        for (int k = i0 ? 2 : 0; k < 8; k++) {
#pragma unroll
          for (int n = 0; n < 8; n++) o[(n >> 1) * 32 + (n & 1) * 1792] = pack_bf16(silu(bf_lo(pend[n])), silu(bf_hi(pend[n])));
#pragma unroll
          for (int n = 0; n < 56; n++) pend[n] = pend[n + 8];
          o += 128;
        }
        bar_arrive(KB_SIG, 288);
      } else if (type == T_P) {
        for (int it = 0; it < cnt; it++) {
          float sx[32], sm[8];
#pragma unroll
          for (int i = 0; i < 32; i++) { sx[i] = 0.f; sm[i & 7] = 0.f; }
          const bool last = it == cnt - 1;
          uint32_t tf[2][56];
#pragma unroll
          for (int p = 0; p < 2; p++) {
            float acc[112];
            zero(acc);
            pass(std::integral_constant<int, 0>(), acc, true, it == 0 && p == 0, last && p == 1 ? 3 : 0, none);
            drain(false);
#pragma unroll
            for (int n = 0; n < 56; n++) tf[p][n] = pack_bf16(acc[2 * n], acc[2 * n + 1]);
            const uint64_t dx = make_desc(sb + K_X + p * 14 * 4096 + wg * 1024, 2048, 128, 0);
            wg_fence();
#pragma unroll
            for (int n = 0; n < 14; n++) wg_rs64(sx, tf[p][4 * n], tf[p][4 * n + 1], tf[p][4 * n + 2], tf[p][4 * n + 3], dx + n * 256, 1);
            wg_commit();
          }
#pragma unroll
          for (int p = 0; p < 2; p++) {
            mbar_wait(sb + K_RF + r.st * 8, r.ph);
            const uint64_t dm = make_desc(sb + K_R + r.st * STG + wg * 7168, 128, 3584, 0);
            wg_fence();
#pragma unroll
            for (int n = 0; n < 14; n++) wg_rs16t(sm, tf[p][4 * n], tf[p][4 * n + 1], tf[p][4 * n + 2], tf[p][4 * n + 3], dm + n * 16, 1);
            wg_commit();
            if (p == 0) { prev = r.st; r.next(); }
          }
          wg_wait<0>();
          if (T == 7) BTIME(27);
          release(prev);
          release(r.st);
          r.next();
          if (lead && last) for (int k = 3; k < 7; k++) mbar_arrive(sb + K_XE + k * 8);
          const bool hi = wq >> 1;
          const int h = i0 + it;
          uint32_t* o = g_P + ((size_t)sseg * 80 * 4 + (wq & 1) * 2) * 32 + l;
#pragma unroll
          for (int rr = 0; rr < 2; rr++) {
            const int tq = (wq & 1) * 16 + rr * 8 + g4;
            float v[10];
#pragma unroll
            for (int n = 0; n < 8; n++) {
              const int idx = (n >> 1) * 4 + rr * 2 + (n & 1);
              const float s = hi ? sx[16 + idx] : sx[idx];
              v[n] = ((n >> 1) * 8 + 2 * c + (n & 1) <= tq) ? s : -1e9f;
            }
            v[8] = hi ? sm[4 + rr * 2] : sm[rr * 2];
            v[9] = hi ? sm[5 + rr * 2] : sm[1 + rr * 2];
            float m = v[0];
#pragma unroll
            for (int n = 1; n < 10; n++) m = fmaxf(m, v[n]);
            m = fmaxf(m, __shfl_xor_sync(0xffffffffu, m, 1));
            m = fmaxf(m, __shfl_xor_sync(0xffffffffu, m, 2));
            float sum = 0.f;
#pragma unroll
            for (int n = 0; n < 10; n++) { v[n] = ex2f((v[n] - m) * 1.4426950408889634f); sum += v[n]; }
            sum += __shfl_xor_sync(0xffffffffu, sum, 1);
            sum += __shfl_xor_sync(0xffffffffu, sum, 2);
            const float inv = rcpf(sum);
#pragma unroll
            for (int n = 0; n < 5; n++)
              o[(n < 4 ? h * 4 + n : 64 + h) * 128 + rr * 32] = pack_bf16(v[2 * n] * inv, v[2 * n + 1] * inv);
          }
          bar_arrive(KB_SIG, 288);
        }
        xph ^= 1;
      } else {
        const bool wide = type == T_FIN;
        const int seg = T * 8 + (wide ? i0 * 2 + rk : i0 >> 1);
        const int mtb = wide ? wg * 4 : (i0 & 1) * 4 + rk * 2 + wg, nmt = wide ? (wg ? 3 : 4) : (mtb < 7 ? 1 : 0);
        { BT0(); mbar_wait(sb + K_XF, xph); BT1(1); }
        float acc[64];
        zero(acc);
        auto stream = [&](auto nt) {
#pragma unroll 1
          for (int st = 0; st < 40; st++) {
            if (st == 12) mbar_wait(sb + K_XF + 16, xph);
            { BT0(); mbar_wait(sb + K_RF + r.st * 8, r.ph); BT1(0); }
            wg_fence();
            const uint64_t da = make_desc(sb + K_R + r.st * STG + wg * 4096, 7168, 128, 0);
            const uint64_t db = make_desc(sb + K_FP + st * 1024, 512, 128, 0);
            wg_ss32<0>(acc, da, db, 1);
            wg_ss32<16>(acc, da + 64, db, 1);
            wg_ss32<32>(acc, da + 128, db, 1);
            if (decltype(nt)::value == 4) wg_ss32<48>(acc, da + 192, db, 1);
            wg_commit();
            { BT0(); wg_wait<1>(); BT1(2); }
            if (st > 0) release(prev);
            prev = r.st;
            r.next();
          }
          wg_wait<0>();
          release(prev);
        };
        if (!wide) {
          prev = r.st;
          mbar_wait(sb + K_XF + 24, xph);
#pragma unroll 1
          for (int st = 0; st < 10; st++) {
            if (st == 3) mbar_wait(sb + K_XF + 16, xph);
            if (st < NST) mbar_wait(sb + K_RF + r.st * 8, r.ph);
            const uint64_t da = make_desc((st < NST ? sb + K_R + r.st * STG : sb + K_NV + (st - NST) * 16384) + wg * 1024, 2048, 128, 0);
            const uint64_t db = make_desc(sb + K_FP + st * 4096, 512, 128, 0);
            wg_fence();
#pragma unroll
            for (int kk = 0; kk < 4; kk++) {
              if (kk & 1) wg_ss32<16>(acc, da + kk * 256, db + kk * 64, 1);
              else wg_ss32<0>(acc, da + kk * 256, db + kk * 64, 1);
            }
            wg_commit();
            if (st < NST) r.next();
          }
          wg_wait<0>();
#pragma unroll 1
          for (int i = 0; i < NST; i++) release(i);
#pragma unroll
          for (int i = 0; i < 16; i++) acc[i] += acc[16 + i];
        } else if (wg == 0) stream(std::integral_constant<int, 4>());
        else stream(std::integral_constant<int, 3>());
        if (!wide) BTIME(31);
        if (lead) for (int k = 0; k < 3; k++) mbar_arrive(sb + K_XE + k * 8);
        BT0();
        mbar_wait(sb + K_XF + 8, xph);
        xph ^= 1;
        const int mi = l >> 3, tr = l & 7;
        const uint32_t xbox = wide ? sb + K_FX + mtb * 4096 : sb + K_NX + wg * 4096;
        const uint32_t gbase = wide ? sb + K_FG + mtb * 1024 : sb + K_NG + wg * 1024, gpitch = wide ? 7168 : 2048;
#pragma unroll
        for (int i = 0; i < 4; i++) {
          if (i < nmt) {
#pragma unroll
            for (int tp = 0; tp < 2; tp++) {
              const int tg = tp * 2 + (mi >> 1), ch = wq * 2 + (mi & 1);
              const uint32_t xa = xbox + i * 4096 + (tg * 8 + tr) * 128 + ((ch ^ tr) << 4);
              uint32_t gq[4], xq[4], oq[4];
              ldsm4t(gq[0], gq[1], gq[2], gq[3], gbase + tg * gpitch + (i * 8 + ch) * 128 + tr * 16);
              ldsm4t(xq[0], xq[1], xq[2], xq[3], xa);
#pragma unroll
              for (int q = 0; q < 4; q++) {
                const uint32_t sp = pack_bf16(acc[i * 16 + tp * 8 + 2 * q], acc[i * 16 + tp * 8 + 2 * q + 1]);
                const uint32_t pr = pack_bf16(bf_lo(sp) * bf_lo(gq[q]), bf_hi(sp) * bf_hi(gq[q]));
                oq[q] = pack_bf16(bf_lo(xq[q]) + bf_lo(pr), bf_hi(xq[q]) + bf_hi(pr));
              }
              stsm4t(xa, oq[0], oq[1], oq[2], oq[3]);
            }
          }
        }
        fence_async_smem();
        bar_sync(KB_WG + wg, 128);
        if (lead) {
          for (int i = 0; i < nmt; i++) tma2d_store(&maps.out, (mtb + i) * 64, seg * SEG, xbox + i * 4096);
          bulk_commit();
          bulk_wait_read();
          for (int k = 3; k < 7; k++) mbar_arrive(sb + K_XE + k * 8);
        }
        BT1(3);
      }
    }
    if (lead) bulk_wait_all();
    BTIME(39);
  }
  __syncthreads();
  asm volatile("barrier.cluster.arrive.relaxed.aligned;\n barrier.cluster.wait.aligned;" ::: "memory");
}
typedef CUresult (*EncodeFn)(CUtensorMap*, CUtensorMapDataType, cuuint32_t, void*, const cuuint64_t*, const cuuint64_t*, const cuuint32_t*,
                             const cuuint32_t*, CUtensorMapInterleave, CUtensorMapSwizzle, CUtensorMapL2promotion, CUtensorMapFloatOOBfill);
static void encode(EncodeFn fn, CUtensorMap* m, const void* p, int cols, int rows, int bc, int br) {
  cuuint64_t gd[2] = {(cuuint64_t)cols, (cuuint64_t)rows}, gs[1] = {(cuuint64_t)cols * 2};
  cuuint32_t bd[2] = {(cuuint32_t)bc, (cuuint32_t)br}, es[2] = {1, 1};
  fn(m, CU_TENSOR_MAP_DATA_TYPE_BFLOAT16, 2, const_cast<void*>(p), gd, gs, bd, es, CU_TENSOR_MAP_INTERLEAVE_NONE, CU_TENSOR_MAP_SWIZZLE_128B,
     CU_TENSOR_MAP_L2_PROMOTION_L2_256B, CU_TENSOR_MAP_FLOAT_OOB_FILL_NONE);
}

struct Model { double step, start, tln, tb, ta, d[6], dx, lead, f1, f2; int uc, fc, open, pc; double pl, fl; };
static double build_schedule(Schedule* sc, int np, const Model& m) {
  struct Ch { int type, T, i0, cnt; double end; bool done; };
  Ch ch[512];
  int n = 0;
  int singles = m.open ? np : 0;
  for (int T = 0; T < 8; T++) {
    for (int i = 0; i < 32; i += (T == 0 ? 1 : m.uc)) ch[n++] = {T_U, T, i, T == 0 ? 1 : (32 - i < m.uc ? 32 - i : m.uc), 0, false};
    for (int i = 0; i < 14;) {
      const int c = singles > 0 ? 1 : (14 - i < m.fc + 2 && 14 - i > m.fc ? (15 - i) / 2 : (14 - i < m.fc ? 14 - i : m.fc));
      ch[n++] = {T_FFN1, T, i, c, 0, false};
      i += c;
      singles--;
    }
    for (int i = 0; i < 2; i++) ch[n++] = {T_FFN2, T, i, 1, 0, false};
    for (int i = 0; i < 16; i += (T < 6 ? m.pc : 1)) ch[n++] = {T_P, T, i, T < 6 ? m.pc : 1, 0, false};
    if (T < 7) for (int i = 0; i < 4; i++) ch[n++] = {T_FIN, T, i, 1, 0, false};
    else for (int i = 0; i < 16; i++) ch[n++] = {T_FINN, T, i, 1, 0, false};
  }
  double t[MAX_PAIRS];
  int len[MAX_PAIRS];
  for (int p = 0; p < MAX_PAIRS; p++) { t[p] = m.tln; len[p] = 0; for (int c = 0; c < MAX_CHUNKS; c++) sc->c[p][c] = T_END << 13; }
  auto fin = [&](int type, int T) {
    double e = 0;
    for (int i = 0; i < n; i++) if (ch[i].type == type && ch[i].T == T) { if (!ch[i].done) return -1.0; if (ch[i].end > e) e = ch[i].end; }
    return e;
  };
  auto chain = [&](int s) { return m.start + m.step * (s + 1) + 0.8; };
  double last = 0;
  for (int left = n; left > 0; left--) {
    int p = 0;
    for (int q = 1; q < np; q++) if (t[q] < t[p]) p = q;
    int best = -1;
    double bs = 0, bk = 0;
    for (int i = 0; i < n; i++) {
      Ch& c = ch[i];
      if (c.done) continue;
      double r = m.tln, dl;
      const double dur = m.d[c.type] * c.cnt, tend = chain(c.T * 8 + 7);
      if (c.type == T_U) { r = m.tb; dl = m.start + m.step * (8 * c.T - 2) - dur - m.lead; if (c.T > 0 && fin(T_U, c.T - 1) < 0) continue; }
      else if (c.type == T_FFN1) dl = tend - m.f1 - dur - (c.cnt == 1 ? 100 : 0);
      else if (c.type == T_FFN2) { r = fin(T_FFN1, c.T); if (r < 0) continue; dl = tend - m.f2 - dur; }
      else if (c.type == T_P) {
        if (fin(T_U, c.T) < 0 || (c.T < 7 && fin(T_U, c.T + 1) < 0)) continue;
        r = tend - m.step - 0.8 * m.d[T_P]; if (r < m.ta) r = m.ta; dl = tend + m.pl;
      } else {
        const double a = fin(T_P, c.T), b = fin(T_FFN2, c.T);
        if (a < 0 || b < 0) continue;
        if (c.type == T_FINN && left > 16) continue;
        r = c.type == T_FINN ? 0 : (a > b ? a : b) - 0.5; dl = tend + m.fl - (c.type == T_FINN ? c.i0 * 0.01 : 0);
      }
      const double s = r > t[p] ? r : t[p], slack = c.type == T_U && c.T == 0 && (len[p] > 0 || !m.open) ? 8.0 : 0.3;
      const double key = s - t[p] > slack ? 1000 + s : (slack > 1 ? -1000 : dl);
      if (best < 0 || key < bk) { best = i; bk = key; bs = s; }
    }
    Ch& c = ch[best];
    c.done = true;
    c.end = bs + m.dx + m.d[c.type] * c.cnt * (c.type == T_FFN2 && c.i0 ? 0.78 : 1.0);
    if (c.type == T_FINN) c.end = chain(63) + m.d[T_FINN];
    if (c.type == T_P && c.end < chain(c.T * 8 + 6) + 2.5 + (c.cnt - 1) * m.d[T_P]) c.end = chain(c.T * 8 + 6) + 2.5 + (c.cnt - 1) * m.d[T_P];
    t[p] = c.end;
    if (c.end > last) last = c.end;
    if (len[p] < MAX_CHUNKS - 1) sc->c[p][len[p]++] = (uint16_t)((c.type << 13) | (c.T << 10) | (c.i0 << 4) | c.cnt);
  }
  return last;
}

static Model g_model = {1.803, 19.2, 8.5, 13.1, 19.0, {6.17, 4.11, 9.79, 20.1, 11.6, 4.0}, 0.44, 9.7, 58, 30, 3, 4, 0, 1, -1.2, 21.3};
static bool g_ready = false;
static ChainMaps g_cm;
static BulkMaps g_bm;
static Schedule g_sched;
static int g_npairs = 34;

extern "C" void kernel_launch(void* const* d_in, const int* in_sizes, int n_in, void* d_out, int out_size) {
  if (!g_ready) {
    void* f = nullptr;
    cudaDriverEntryPointQueryResult q;
    cudaGetDriverEntryPoint("cuTensorMapEncodeTiled", &f, cudaEnableDefault, &q);
    EncodeFn fn = (EncodeFn)f;
    encode(fn, &g_cm.wq, d_in[2], NH * DH, DM, 64, 112);
    encode(fn, &g_cm.wk, d_in[3], NH * DH, DM, 64, 128);
    encode(fn, &g_cm.wv, d_in[4], NH * DH, DM, 64, 112);
    encode(fn, &g_cm.wo, d_in[5], DM, NH * DH, 64, 64);
    encode(fn, &g_bm.wg, d_in[8], FF, DM, 64, 32);
    encode(fn, &g_bm.wu, d_in[9], FF, DM, 64, 32);
    encode(fn, &g_bm.wd, d_in[10], DM, FF, 64, 32);
    encode(fn, &g_bm.x, d_in[0], DM, SEQ, 64, 32);
    encode(fn, &g_bm.out, d_out, DM, SEQ, 64, 32);
    for (int i = 0; i < 2; i++) {
      void* p = nullptr;
      if (i) cudaGetSymbolAddress(&p, g_B); else cudaGetSymbolAddress(&p, g_A);
      cuuint64_t gd[2] = {448, NH * 2 * 56}, gs[1] = {3584};
      cuuint32_t bd[2] = {224, 14}, es[2] = {1, 1};
      fn(i ? &g_cm.gb : &g_cm.ga, CU_TENSOR_MAP_DATA_TYPE_UINT64, 2, p, gd, gs, bd, es, CU_TENSOR_MAP_INTERLEAVE_NONE, CU_TENSOR_MAP_SWIZZLE_NONE,
         CU_TENSOR_MAP_L2_PROMOTION_NONE, CU_TENSOR_MAP_FLOAT_OOB_FILL_NONE);
    }
    {
      void* p = nullptr;
      cudaGetSymbolAddress(&p, g_Vt);
      cuuint64_t gd[2] = {896, NSEG * 80}, gs[1] = {7168};
      cuuint32_t bd[2] = {256, 8}, es[2] = {1, 1};
      fn(&g_bm.vt, CU_TENSOR_MAP_DATA_TYPE_UINT64, 2, p, gd, gs, bd, es, CU_TENSOR_MAP_INTERLEAVE_NONE, CU_TENSOR_MAP_SWIZZLE_NONE,
         CU_TENSOR_MAP_L2_PROMOTION_L2_256B, CU_TENSOR_MAP_FLOAT_OOB_FILL_NONE);
    }
    cudaFuncSetAttribute(chain_kernel, cudaFuncAttributeNonPortableClusterSizeAllowed, 1);
    cudaFuncSetAttribute(chain_kernel, cudaFuncAttributeMaxDynamicSharedMemorySize, C_SMEM);
    cudaFuncSetAttribute(bulk_kernel, cudaFuncAttributeMaxDynamicSharedMemorySize, K_SMEM);
    int sms = 132;
    cudaDeviceGetAttribute(&sms, cudaDevAttrMultiProcessorCount, 0);
    g_npairs = (sms - 64) / 2;
    if (g_npairs > MAX_PAIRS) g_npairs = MAX_PAIRS;
    build_schedule(&g_sched, g_npairs, g_model);
    g_ready = true;
  }
  cudaStream_t st = cudaStreamPerThread;
  chain_kernel<<<64, 384, C_SMEM, st>>>(g_cm, (const __nv_bfloat16*)d_in[1]);
  cudaLaunchConfig_t cfg = {};
  cfg.gridDim = dim3(2 * g_npairs);
  cfg.blockDim = dim3(384);
  cfg.dynamicSmemBytes = K_SMEM;
  cfg.stream = st;
  cudaLaunchAttribute at[1];
  at[0].id = cudaLaunchAttributeProgrammaticStreamSerialization;
  at[0].val.programmaticStreamSerializationAllowed = 1;
  cfg.attrs = at;
  cfg.numAttrs = 1;
  cudaLaunchKernelEx(&cfg, bulk_kernel, g_bm, g_sched, (const __nv_bfloat16*)d_in[0]);
}
```
